```python
import torch

def _softmax(x, axis=-1):
    return torch.softmax(x, dim=axis)
def _gelu(x):
    return torch.nn.functional.gelu(x, approximate="tanh")
def _silu(x):
    return torch.nn.functional.silu(x)
def _sigmoid(x):
    return torch.sigmoid(x)
def _layernorm(x, axis=-1, eps=1e-5):
    m = x.mean(dim=axis, keepdim=True)
    v = x.var(dim=axis, keepdim=True, unbiased=False)
    return (x - m) / torch.sqrt(v + eps)
def _scatter_add(tgt, idx, src, axis=0):
    return tgt.clone().index_add_(axis, idx, src)
def _segment_sum(src, seg, n):
    out = torch.zeros((n,) + src.shape[1:], dtype=src.dtype)
    return out.index_add_(0, seg, src)
def _pad(x, pw):
    flat = tuple(v for pair in reversed(pw) for v in pair)
    return torch.nn.functional.pad(x, flat)

kernel_name = 'concat_heads__softmax_full_mha__grouped_kv_mqa__prompt'

def setup_inputs():

    _w = (lambda a: (lambda t: t.to(torch.bfloat16) if t.is_floating_point() else t)(torch.as_tensor(a)))
    def _A_setup():
        B, S, D = 1, 2048, 1024
        return {
            "x": _w((lambda *s: torch.randn(*s, dtype=torch.bfloat16) * 0.2)(B, S, D)),
            "wqkv": _w((lambda *s: torch.randn(*s, dtype=torch.bfloat16) * 0.2)(D, 3 * D)),
            "wo": _w((lambda *s: torch.randn(*s, dtype=torch.bfloat16) * 0.05)(D, D)),
        }
    _A_in = _A_setup()

    def _B_setup():
        B, S, D, H = 1, 2048, 1024, 32
        Dh = D // H
        return {
            "x": _w((lambda *s: torch.randn(*s, dtype=torch.bfloat16) * 0.05)(B, S, D)),
            "wq": _w((lambda *s: torch.randn(*s, dtype=torch.bfloat16) * 0.8)(D, H * Dh)),
            "wk": _w((lambda *s: torch.randn(*s, dtype=torch.bfloat16) * 0.8)(D, Dh)),
            "wv": _w((lambda *s: torch.randn(*s, dtype=torch.bfloat16) * 0.1)(D, Dh)),
            "wo": _w((lambda *s: torch.randn(*s, dtype=torch.bfloat16) * 0.1)(H * Dh, D)),
        }
    _B_in = _B_setup()

    return {
        "A_x": _A_in["x"],
        "A_wqkv": _A_in["wqkv"],
        "A_wo": _A_in["wo"],
        "B_x": _B_in["x"],
        "B_wq": _B_in["wq"],
        "B_wk": _B_in["wk"],
        "B_wv": _B_in["wv"],
        "B_wo": _B_in["wo"],
    }

def reference(A_x, A_wqkv, A_wo, B_x, B_wq, B_wk, B_wv, B_wo):
    def _A_ref(x, wqkv, wo):
        B, S, D = x.shape
        H = 32; Dh = D // H
        qkv = (lambda x, *d: x.permute(*d))((x @ wqkv).reshape(B, S, 3, H, Dh), 2, 0, 3, 1, 4)
        q, k, v = qkv[0], qkv[1], qkv[2]
        scale = Dh ** -0.5
        scores = torch.einsum("bhqd,bhkd->bhqk", q, k) * scale
        p = _softmax(scores, axis=-1)
        o = torch.einsum("bhqk,bhkd->bhqd", p, v)
        return (lambda x, *d: x.permute(*d))(o, 0, 2, 1, 3).reshape(B, S, D) @ wo

    def _B_ref(x, wq, wk, wv, wo):
        B, S, D = x.shape
        H = 32
        Dh = D // H
        q = (lambda x, *d: x.permute(*d))((x @ wq).reshape(B, S, H, Dh), 0, 2, 1, 3)
        k = x @ wk
        v = x @ wv
        scores = torch.einsum("bhqd,bkd->bhqk", q, k) * (Dh ** -0.5)
        p = _softmax(scores, axis=-1)
        o = torch.einsum("bhqk,bkd->bhqd", p, v)
        return (lambda x, *d: x.permute(*d))(o, 0, 2, 1, 3).reshape(B, S, H * Dh) @ wo

    a = _A_ref(A_x, A_wqkv, A_wo)
    b = _B_ref(B_x, B_wq, B_wk, B_wv, B_wo)
    return torch.concatenate([a, b], axis=-1)
```

```cpp
#include <cuda_runtime.h>
#include <cuda_bf16.h>
#include <cuda.h>
#include <stdint.h>

namespace {

constexpr int SEQ = 2048;
constexpr int QKV_LD = 4160;
constexpr int O_LD = 2048;
constexpr int NHEADCOL = QKV_LD / 32;
constexpr float QSCALE = 0.17677669529663687f * 1.4426950408889634f;

__device__ __align__(1024) __nv_bfloat16 g_qkv[SEQ * QKV_LD];
__device__ __align__(1024) __nv_bfloat16 g_o[SEQ * O_LD];
__device__ __align__(16) float g_nrm[NHEADCOL * 128];

__device__ __forceinline__ uint32_t smem_u32(const void* p) { return (uint32_t)__cvta_generic_to_shared(p); }
__device__ __forceinline__ void mbar_init(uint32_t bar, uint32_t count) {
  asm volatile("mbarrier.init.shared::cta.b64 [%0], %1;" ::"r"(bar), "r"(count) : "memory");
}
__device__ __forceinline__ void mbar_expect_tx(uint32_t bar, uint32_t bytes) {
  asm volatile("mbarrier.arrive.expect_tx.shared::cta.b64 _, [%0], %1;" ::"r"(bar), "r"(bytes) : "memory");
}
__device__ __forceinline__ void mbar_arrive(uint32_t bar) {
  asm volatile("mbarrier.arrive.shared::cta.b64 _, [%0];" ::"r"(bar) : "memory");
}
__device__ __forceinline__ void mbar_arrive_remote(uint32_t bar, uint32_t cta) {
  asm volatile("{\n.reg .b32 ra;\nmapa.shared::cluster.u32 ra, %0, %1;\n"
               "mbarrier.arrive.release.cluster.shared::cluster.b64 _, [ra];\n}\n" ::"r"(bar), "r"(cta) : "memory");
}
__device__ __forceinline__ uint32_t mbar_try(uint32_t bar, uint32_t parity) {
  uint32_t ok;
  asm volatile("{\n.reg .pred p;\nmbarrier.try_wait.parity.shared::cta.b64 p, [%1], %2;\nselp.u32 %0, 1, 0, p;\n}\n"
               : "=r"(ok) : "r"(bar), "r"(parity) : "memory");
  return ok;
}
__device__ __forceinline__ void mbar_wait(uint32_t bar, uint32_t parity) {
  uint32_t n = 0;
#pragma unroll 1
  while (!mbar_try(bar, parity)) {
    if (++n > (1u << 24)) __trap();
  }
}
__device__ __forceinline__ void tma_load_2d(uint32_t dst, const CUtensorMap* map, uint32_t bar, int c0, int c1) {
  asm volatile("cp.async.bulk.tensor.2d.shared::cluster.global.mbarrier::complete_tx::bytes [%0], [%1, {%3, %4}], [%2];"
               ::"r"(dst), "l"(map), "r"(bar), "r"(c0), "r"(c1) : "memory");
}
__device__ __forceinline__ void tma_load_2d_mc(uint32_t dst, const CUtensorMap* map, uint32_t bar, int c0, int c1, uint16_t mask) {
  asm volatile("cp.async.bulk.tensor.2d.shared::cluster.global.mbarrier::complete_tx::bytes.multicast::cluster [%0], [%1, {%3, %4}], [%2], %5;"
               ::"r"(dst), "l"(map), "r"(bar), "r"(c0), "r"(c1), "h"(mask) : "memory");
}
__device__ __forceinline__ void tma_store_2d(const CUtensorMap* map, uint32_t src, int c0, int c1) {
  asm volatile("cp.async.bulk.tensor.2d.global.shared::cta.bulk_group [%0, {%2, %3}], [%1];"
               ::"l"(map), "r"(src), "r"(c0), "r"(c1) : "memory");
}
__device__ __forceinline__ void bulk_commit() { asm volatile("cp.async.bulk.commit_group;" ::: "memory"); }
template <int N> __device__ __forceinline__ void bulk_wait_read() {
  asm volatile("cp.async.bulk.wait_group.read %0;" ::"n"(N) : "memory");
}
template <int N> __device__ __forceinline__ void bulk_wait() {
  asm volatile("cp.async.bulk.wait_group %0;" ::"n"(N) : "memory");
}
__device__ __forceinline__ void prefetch_tmap(const CUtensorMap* map) {
  asm volatile("prefetch.tensormap [%0];" ::"l"(map) : "memory");
}
__device__ __forceinline__ void fence_proxy_async() { asm volatile("fence.proxy.async.shared::cta;" ::: "memory"); }
__device__ __forceinline__ void fence_mbar_init() { asm volatile("fence.mbarrier_init.release.cluster;" ::: "memory"); }
__device__ __forceinline__ void cluster_sync() {
  asm volatile("barrier.cluster.arrive.release.aligned;\nbarrier.cluster.wait.acquire.aligned;" ::: "memory");
}
__device__ __forceinline__ void bar_sync(int id, int n) { asm volatile("bar.sync %0, %1;" ::"r"(id), "r"(n) : "memory"); }
__device__ __forceinline__ void pdl_wait() { asm volatile("griddepcontrol.wait;" ::: "memory"); }
__device__ __forceinline__ void pdl_launch() { asm volatile("griddepcontrol.launch_dependents;" ::: "memory"); }
__device__ __forceinline__ void wg_fence() { asm volatile("wgmma.fence.sync.aligned;" ::: "memory"); }
__device__ __forceinline__ void wg_commit() { asm volatile("wgmma.commit_group.sync.aligned;" ::: "memory"); }
template <int N> __device__ __forceinline__ void wg_wait() {
  asm volatile("wgmma.wait_group.sync.aligned %0;" ::"n"(N) : "memory");
}
__device__ __forceinline__ void stmatrix_x4(uint32_t addr, uint32_t r0, uint32_t r1, uint32_t r2, uint32_t r3) {
  asm volatile("stmatrix.sync.aligned.m8n8.x4.shared.b16 [%0], {%1, %2, %3, %4};"
               ::"r"(addr), "r"(r0), "r"(r1), "r"(r2), "r"(r3) : "memory");
}
__device__ __forceinline__ void ldmatrix_x4(uint32_t addr, uint32_t& r0, uint32_t& r1, uint32_t& r2, uint32_t& r3) {
  asm volatile("ldmatrix.sync.aligned.m8n8.x4.shared.b16 {%0, %1, %2, %3}, [%4];"
               : "=r"(r0), "=r"(r1), "=r"(r2), "=r"(r3) : "r"(addr) : "memory");
}
__device__ __forceinline__ uint32_t pack_bf16(float lo, float hi) {
  uint32_t r;
  asm("cvt.rn.bf16x2.f32 %0, %1, %2;" : "=r"(r) : "f"(hi), "f"(lo));
  return r;
}
__device__ __forceinline__ float ex2(float x) {
  float y;
  asm("ex2.approx.ftz.f32 %0, %1;" : "=f"(y) : "f"(x));
  return y;
}
__device__ __forceinline__ float rcp(float x) {
  float y;
  asm("rcp.approx.ftz.f32 %0, %1;" : "=f"(y) : "f"(x));
  return y;
}
__device__ __forceinline__ uint64_t make_desc(uint32_t addr, uint32_t lbo, uint32_t sbo, uint32_t swz) {
  return (uint64_t)((addr & 0x3FFFF) >> 4) | ((uint64_t)((lbo & 0x3FFFF) >> 4) << 16) | ((uint64_t)((sbo & 0x3FFFF) >> 4) << 32) |
         ((uint64_t)swz << 62);
}
template <int R> __device__ __forceinline__ void fence_regs(float (&d)[R]) {
#pragma unroll
  for (int i = 0; i < R; i++) asm volatile("" : "+f"(d[i])::"memory");
}

__device__ __forceinline__ void wgmma_n256_ss_tb(float (&d)[128], uint64_t descA, uint64_t descB, int scaleD) {
  asm volatile("{\n.reg .pred p;\nsetp.ne.b32 p, %130, 0;\n"
    "wgmma.mma_async.sync.aligned.m64n256k16.f32.bf16.bf16 "
    "{%0, %1, %2, %3, %4, %5, %6, %7, %8, %9, %10, %11, %12, %13, %14, %15, %16, %17, %18, %19, %20, %21, %22, %23, %24, %25, %26, %27, %28, %29, %30, %31, %32, %33, %34, %35, %36, %37, %38, %39, %40, %41, %42, %43, %44, %45, %46, %47, %48, %49, %50, %51, %52, %53, %54, %55, %56, %57, %58, %59, %60, %61, %62, %63, %64, %65, %66, %67, %68, %69, %70, %71, %72, %73, %74, %75, %76, %77, %78, %79, %80, %81, %82, %83, %84, %85, %86, %87, %88, %89, %90, %91, %92, %93, %94, %95, %96, %97, %98, %99, %100, %101, %102, %103, %104, %105, %106, %107, %108, %109, %110, %111, %112, %113, %114, %115, %116, %117, %118, %119, %120, %121, %122, %123, %124, %125, %126, %127}, "
    "%128, %129, p, 1, 1, 0, 1;\n}\n"
    : "+f"(d[0]), "+f"(d[1]), "+f"(d[2]), "+f"(d[3]), "+f"(d[4]), "+f"(d[5]), "+f"(d[6]), "+f"(d[7]), "+f"(d[8]), "+f"(d[9]), "+f"(d[10]), "+f"(d[11]), "+f"(d[12]), "+f"(d[13]), "+f"(d[14]), "+f"(d[15]), "+f"(d[16]), "+f"(d[17]), "+f"(d[18]), "+f"(d[19]), "+f"(d[20]), "+f"(d[21]), "+f"(d[22]), "+f"(d[23]), "+f"(d[24]), "+f"(d[25]), "+f"(d[26]), "+f"(d[27]), "+f"(d[28]), "+f"(d[29]), "+f"(d[30]), "+f"(d[31]), "+f"(d[32]), "+f"(d[33]), "+f"(d[34]), "+f"(d[35]), "+f"(d[36]), "+f"(d[37]), "+f"(d[38]), "+f"(d[39]), "+f"(d[40]), "+f"(d[41]), "+f"(d[42]), "+f"(d[43]), "+f"(d[44]), "+f"(d[45]), "+f"(d[46]), "+f"(d[47]), "+f"(d[48]), "+f"(d[49]), "+f"(d[50]), "+f"(d[51]), "+f"(d[52]), "+f"(d[53]), "+f"(d[54]), "+f"(d[55]), "+f"(d[56]), "+f"(d[57]), "+f"(d[58]), "+f"(d[59]), "+f"(d[60]), "+f"(d[61]), "+f"(d[62]), "+f"(d[63]), "+f"(d[64]), "+f"(d[65]), "+f"(d[66]), "+f"(d[67]), "+f"(d[68]), "+f"(d[69]), "+f"(d[70]), "+f"(d[71]), "+f"(d[72]), "+f"(d[73]), "+f"(d[74]), "+f"(d[75]), "+f"(d[76]), "+f"(d[77]), "+f"(d[78]), "+f"(d[79]), "+f"(d[80]), "+f"(d[81]), "+f"(d[82]), "+f"(d[83]), "+f"(d[84]), "+f"(d[85]), "+f"(d[86]), "+f"(d[87]), "+f"(d[88]), "+f"(d[89]), "+f"(d[90]), "+f"(d[91]), "+f"(d[92]), "+f"(d[93]), "+f"(d[94]), "+f"(d[95]), "+f"(d[96]), "+f"(d[97]), "+f"(d[98]), "+f"(d[99]), "+f"(d[100]), "+f"(d[101]), "+f"(d[102]), "+f"(d[103]), "+f"(d[104]), "+f"(d[105]), "+f"(d[106]), "+f"(d[107]), "+f"(d[108]), "+f"(d[109]), "+f"(d[110]), "+f"(d[111]), "+f"(d[112]), "+f"(d[113]), "+f"(d[114]), "+f"(d[115]), "+f"(d[116]), "+f"(d[117]), "+f"(d[118]), "+f"(d[119]), "+f"(d[120]), "+f"(d[121]), "+f"(d[122]), "+f"(d[123]), "+f"(d[124]), "+f"(d[125]), "+f"(d[126]), "+f"(d[127])
    : "l"(descA), "l"(descB), "r"(scaleD));
}
__device__ __forceinline__ void wgmma_n64_ss_tb(float (&d)[32], uint64_t descA, uint64_t descB, int scaleD) {
  asm volatile("{\n.reg .pred p;\nsetp.ne.b32 p, %34, 0;\n"
    "wgmma.mma_async.sync.aligned.m64n64k16.f32.bf16.bf16 "
    "{%0, %1, %2, %3, %4, %5, %6, %7, %8, %9, %10, %11, %12, %13, %14, %15, %16, %17, %18, %19, %20, %21, %22, %23, %24, %25, %26, %27, %28, %29, %30, %31}, "
    "%32, %33, p, 1, 1, 0, 1;\n}\n"
    : "+f"(d[0]), "+f"(d[1]), "+f"(d[2]), "+f"(d[3]), "+f"(d[4]), "+f"(d[5]), "+f"(d[6]), "+f"(d[7]), "+f"(d[8]), "+f"(d[9]), "+f"(d[10]), "+f"(d[11]), "+f"(d[12]), "+f"(d[13]), "+f"(d[14]), "+f"(d[15]), "+f"(d[16]), "+f"(d[17]), "+f"(d[18]), "+f"(d[19]), "+f"(d[20]), "+f"(d[21]), "+f"(d[22]), "+f"(d[23]), "+f"(d[24]), "+f"(d[25]), "+f"(d[26]), "+f"(d[27]), "+f"(d[28]), "+f"(d[29]), "+f"(d[30]), "+f"(d[31])
    : "l"(descA), "l"(descB), "r"(scaleD));
}
__device__ __forceinline__ void wgmma_n128_rs(float (&d)[64], uint32_t a0, uint32_t a1, uint32_t a2, uint32_t a3, uint64_t descB, int scaleD) {
  asm volatile("{\n.reg .pred p;\nsetp.ne.b32 p, %69, 0;\n"
    "wgmma.mma_async.sync.aligned.m64n128k16.f32.bf16.bf16 "
    "{%0, %1, %2, %3, %4, %5, %6, %7, %8, %9, %10, %11, %12, %13, %14, %15, %16, %17, %18, %19, %20, %21, %22, %23, %24, %25, %26, %27, %28, %29, %30, %31, %32, %33, %34, %35, %36, %37, %38, %39, %40, %41, %42, %43, %44, %45, %46, %47, %48, %49, %50, %51, %52, %53, %54, %55, %56, %57, %58, %59, %60, %61, %62, %63}, "
    "{%64, %65, %66, %67}, %68, p, 1, 1, 0;\n}\n"
    : "+f"(d[0]), "+f"(d[1]), "+f"(d[2]), "+f"(d[3]), "+f"(d[4]), "+f"(d[5]), "+f"(d[6]), "+f"(d[7]), "+f"(d[8]), "+f"(d[9]), "+f"(d[10]), "+f"(d[11]), "+f"(d[12]), "+f"(d[13]), "+f"(d[14]), "+f"(d[15]), "+f"(d[16]), "+f"(d[17]), "+f"(d[18]), "+f"(d[19]), "+f"(d[20]), "+f"(d[21]), "+f"(d[22]), "+f"(d[23]), "+f"(d[24]), "+f"(d[25]), "+f"(d[26]), "+f"(d[27]), "+f"(d[28]), "+f"(d[29]), "+f"(d[30]), "+f"(d[31]), "+f"(d[32]), "+f"(d[33]), "+f"(d[34]), "+f"(d[35]), "+f"(d[36]), "+f"(d[37]), "+f"(d[38]), "+f"(d[39]), "+f"(d[40]), "+f"(d[41]), "+f"(d[42]), "+f"(d[43]), "+f"(d[44]), "+f"(d[45]), "+f"(d[46]), "+f"(d[47]), "+f"(d[48]), "+f"(d[49]), "+f"(d[50]), "+f"(d[51]), "+f"(d[52]), "+f"(d[53]), "+f"(d[54]), "+f"(d[55]), "+f"(d[56]), "+f"(d[57]), "+f"(d[58]), "+f"(d[59]), "+f"(d[60]), "+f"(d[61]), "+f"(d[62]), "+f"(d[63])
    : "r"(a0), "r"(a1), "r"(a2), "r"(a3), "l"(descB), "r"(scaleD));
}
__device__ __forceinline__ void wgmma_n64_rs(float (&d)[32], uint32_t a0, uint32_t a1, uint32_t a2, uint32_t a3, uint64_t descB, int scaleD) {
  asm volatile("{\n.reg .pred p;\nsetp.ne.b32 p, %37, 0;\n"
    "wgmma.mma_async.sync.aligned.m64n64k16.f32.bf16.bf16 "
    "{%0, %1, %2, %3, %4, %5, %6, %7, %8, %9, %10, %11, %12, %13, %14, %15, %16, %17, %18, %19, %20, %21, %22, %23, %24, %25, %26, %27, %28, %29, %30, %31}, "
    "{%32, %33, %34, %35}, %36, p, 1, 1, 0;\n}\n"
    : "+f"(d[0]), "+f"(d[1]), "+f"(d[2]), "+f"(d[3]), "+f"(d[4]), "+f"(d[5]), "+f"(d[6]), "+f"(d[7]), "+f"(d[8]), "+f"(d[9]), "+f"(d[10]), "+f"(d[11]), "+f"(d[12]), "+f"(d[13]), "+f"(d[14]), "+f"(d[15]), "+f"(d[16]), "+f"(d[17]), "+f"(d[18]), "+f"(d[19]), "+f"(d[20]), "+f"(d[21]), "+f"(d[22]), "+f"(d[23]), "+f"(d[24]), "+f"(d[25]), "+f"(d[26]), "+f"(d[27]), "+f"(d[28]), "+f"(d[29]), "+f"(d[30]), "+f"(d[31])
    : "r"(a0), "r"(a1), "r"(a2), "r"(a3), "l"(descB), "r"(scaleD));
}
__device__ __forceinline__ void wgmma_n40_rs_tb(float (&d)[20], uint32_t a0, uint32_t a1, uint32_t a2, uint32_t a3, uint64_t descB, int scaleD) {
  asm volatile("{\n.reg .pred p;\nsetp.ne.b32 p, %25, 0;\n"
    "wgmma.mma_async.sync.aligned.m64n40k16.f32.bf16.bf16 "
    "{%0, %1, %2, %3, %4, %5, %6, %7, %8, %9, %10, %11, %12, %13, %14, %15, %16, %17, %18, %19}, "
    "{%20, %21, %22, %23}, %24, p, 1, 1, 1;\n}\n"
    : "+f"(d[0]), "+f"(d[1]), "+f"(d[2]), "+f"(d[3]), "+f"(d[4]), "+f"(d[5]), "+f"(d[6]), "+f"(d[7]), "+f"(d[8]), "+f"(d[9]), "+f"(d[10]), "+f"(d[11]), "+f"(d[12]), "+f"(d[13]), "+f"(d[14]), "+f"(d[15]), "+f"(d[16]), "+f"(d[17]), "+f"(d[18]), "+f"(d[19])
    : "r"(a0), "r"(a1), "r"(a2), "r"(a3), "l"(descB), "r"(scaleD));
}
struct GemmMaps { CUtensorMap a0, a1, w0, w1, w2, w3, out; };

constexpr int G_STAGES = 4;
constexpr int G_STAGE_BYTES = 49152;
constexpr int G_STG_OFF = G_STAGES * G_STAGE_BYTES;
constexpr int G_BAR_OFF = G_STG_OFF + 32768;
constexpr int G_SMEM = G_BAR_OFF + 128 + 1024;
constexpr int G_THREADS = 288;

struct Tile { const CUtensorMap* a; const CUtensorMap* w; int a_k0, row0, w_col, out_col; float scale; };

template <int MODE>
__device__ __forceinline__ Tile get_tile(const GemmMaps& m, int c, int rank, int it) {
  Tile t;
  if (MODE == 0) {
    int p = c + 64 * it;
    if (p < 96) {
      int nt = p >> 3;
      t.a = &m.a0; t.w = &m.w0; t.w_col = nt * 256; t.out_col = nt * 256; t.scale = nt < 4 ? QSCALE : 1.0f;
      t.row0 = (p & 7) * 256 + rank * 128;
    } else {
      int q = p - 96, nt = q >> 3;
      t.a = &m.a1; t.w = &m.w1; t.w_col = nt * 256; t.out_col = 3072 + nt * 256; t.scale = QSCALE;
      t.row0 = (q & 7) * 256 + rank * 128;
    }
    t.a_k0 = 0;
  } else {
    int b = c >> 5, q = c & 31, nt = q >> 3;
    t.a = &m.a0; t.w = b ? &m.w1 : &m.w0; t.a_k0 = b * 1024; t.w_col = nt * 256; t.out_col = b * 1024 + nt * 256;
    t.row0 = (q & 7) * 256 + rank * 128; t.scale = 1.0f;
  }
  return t;
}

template <int NG, int R>
__device__ __forceinline__ void write_norms(const float (&acc)[R], float scale, int colgroup0, int rowblock, int lane) {
#pragma unroll
  for (int hh = 0; hh < NG; hh++) {
    float s0 = 0.f, s1 = 0.f;
#pragma unroll
    for (int j = 4 * hh; j < 4 * hh + 4; j++) {
      s0 = fmaf(acc[4 * j], acc[4 * j], s0); s0 = fmaf(acc[4 * j + 1], acc[4 * j + 1], s0);
      s1 = fmaf(acc[4 * j + 2], acc[4 * j + 2], s1); s1 = fmaf(acc[4 * j + 3], acc[4 * j + 3], s1);
    }
    s0 += __shfl_xor_sync(0xffffffffu, s0, 1); s1 += __shfl_xor_sync(0xffffffffu, s1, 1);
    s0 += __shfl_xor_sync(0xffffffffu, s0, 2); s1 += __shfl_xor_sync(0xffffffffu, s1, 2);
    uint32_t u = max(__float_as_uint(s0) & 0x7fffffffu, __float_as_uint(s1) & 0x7fffffffu);
    u = __reduce_max_sync(0xffffffffu, u);
    if (lane == 0) g_nrm[(colgroup0 + hh) * 128 + rowblock] = __uint_as_float(u) * scale * scale;
  }
}

template <int NQ, int R>
__device__ __forceinline__ void store_tile(const float (&acc)[R], float scale, uint32_t stg, const CUtensorMap* omap,
                                           int out_col, int row0, int wg, int wwarp, int lane, int tid_wg) {
  const int mi = lane >> 3;
  const int row = wwarp * 16 + (lane & 7) + (mi & 1) * 8;
#pragma unroll
  for (int q = 0; q < NQ; q++) {
    const uint32_t buf = stg + (q & 1) * 8192;
#pragma unroll
    for (int jj = 0; jj < 4; jj++) {
      const int j = 8 * q + 2 * jj;
      uint32_t r0 = pack_bf16(acc[4 * j] * scale, acc[4 * j + 1] * scale);
      uint32_t r1 = pack_bf16(acc[4 * j + 2] * scale, acc[4 * j + 3] * scale);
      uint32_t r2 = pack_bf16(acc[4 * j + 4] * scale, acc[4 * j + 5] * scale);
      uint32_t r3 = pack_bf16(acc[4 * j + 6] * scale, acc[4 * j + 7] * scale);
      const int chunk = 2 * jj + (mi >> 1);
      stmatrix_x4(buf + row * 128 + ((chunk ^ (row & 7)) << 4), r0, r1, r2, r3);
    }
    fence_proxy_async();
    if (tid_wg == 0) bulk_wait_read<0>();
    bar_sync(1 + wg, 128);
    if (tid_wg == 0) { tma_store_2d(omap, buf, out_col + q * 64, row0 + wg * 64); bulk_commit(); }
  }
}

template <int MODE>
__global__ void __cluster_dims__(2, 1, 1) __launch_bounds__(G_THREADS, 1) gemm_kernel(const __grid_constant__ GemmMaps maps) {
  extern __shared__ uint8_t smem_raw[];
  const uint32_t sbase = (smem_u32(smem_raw) + 1023u) & ~1023u;
  const uint32_t bar_full = sbase + G_BAR_OFF, bar_empty = bar_full + 8 * G_STAGES;
  const int tid = threadIdx.x, warp = tid >> 5, lane = tid & 31;
  const int c = blockIdx.x >> 1, rank = blockIdx.x & 1;
  const bool small = (MODE == 0) && (c >= 64);
  const int ntiles = MODE == 1 ? 1 : (small ? 4 : 2);

  if (tid == 0) {
    for (int s = 0; s < G_STAGES; s++) { mbar_init(bar_full + 8 * s, 1); mbar_init(bar_empty + 8 * s, small ? 8 : 16); }
    fence_mbar_init();
  }
  if (warp == 8 && lane == 0) {
    prefetch_tmap(&maps.a0); prefetch_tmap(&maps.w0); prefetch_tmap(&maps.w1); prefetch_tmap(&maps.out);
    if (MODE == 0) prefetch_tmap(&maps.a1);
  }
  cluster_sync();
  pdl_launch();

  if (warp == 8) {
    if (lane == 0) {
      int s = 0; uint32_t ph = 1;
      if (!small) {
        for (int it = 0; it < ntiles; it++) {
          const Tile t = get_tile<MODE>(maps, c, rank, it);
          int kb0 = 0;
          if (MODE == 1) {
            for (int kb = 0; kb < G_STAGES; kb++) {
              mbar_expect_tx(bar_full + 8 * kb, G_STAGE_BYTES);
              const uint32_t B = sbase + kb * G_STAGE_BYTES + 16384;
              tma_load_2d_mc(B + (2 * rank) * 8192, t.w, bar_full + 8 * kb, t.w_col + (2 * rank) * 64, kb * 64, 3);
              tma_load_2d_mc(B + (2 * rank + 1) * 8192, t.w, bar_full + 8 * kb, t.w_col + (2 * rank + 1) * 64, kb * 64, 3);
            }
            pdl_wait();
            for (int kb = 0; kb < G_STAGES; kb++)
              tma_load_2d(sbase + kb * G_STAGE_BYTES, t.a, bar_full + 8 * kb, t.a_k0 + kb * 64, t.row0);
            kb0 = G_STAGES; ph = 0;
          }
          for (int kb = kb0; kb < 16; kb++) {
            mbar_wait(bar_empty + 8 * s, ph);
            mbar_expect_tx(bar_full + 8 * s, G_STAGE_BYTES);
            const uint32_t A = sbase + s * G_STAGE_BYTES, B = A + 16384;
            tma_load_2d(A, t.a, bar_full + 8 * s, t.a_k0 + kb * 64, t.row0);
            tma_load_2d_mc(B + (2 * rank) * 8192, t.w, bar_full + 8 * s, t.w_col + (2 * rank) * 64, kb * 64, 3);
            tma_load_2d_mc(B + (2 * rank + 1) * 8192, t.w, bar_full + 8 * s, t.w_col + (2 * rank + 1) * 64, kb * 64, 3);
            if (++s == G_STAGES) { s = 0; ph ^= 1; }
          }
        }
      } else {
        const int idx = (c - 64) * 2 + rank;
        for (int it = 0; it < 4; it++) {
          const int row0 = (idx * 4 + it) * 128;
          for (int kb = 0; kb < 16; kb++) {
            mbar_wait(bar_empty + 8 * s, ph);
            mbar_expect_tx(bar_full + 8 * s, 16384 + 8192);
            const uint32_t A = sbase + s * G_STAGE_BYTES, B = A + 16384;
            tma_load_2d(A, &maps.a1, bar_full + 8 * s, kb * 64, row0);
            tma_load_2d(B, &maps.w2, bar_full + 8 * s, 0, kb * 64);
            tma_load_2d(B + 4096, &maps.w3, bar_full + 8 * s, 0, kb * 64);
            if (++s == G_STAGES) { s = 0; ph ^= 1; }
          }
        }
      }
    }
  } else {
    const int wg = warp >> 2, wwarp = warp & 3, tid_wg = tid & 127;
    const uint32_t stg = sbase + G_STG_OFF + wg * 16384;
    int s = 0; uint32_t ph = 0;
    if (!small) {
      for (int it = 0; it < ntiles; it++) {
        const Tile t = get_tile<MODE>(maps, c, rank, it);
        float acc[128];
        int prev = -1;
#pragma unroll 1
        for (int kb = 0; kb < 16; kb++) {
          mbar_wait(bar_full + 8 * s, ph);
          const uint32_t A = sbase + s * G_STAGE_BYTES + wg * 8192, B = sbase + s * G_STAGE_BYTES + 16384;
          const uint64_t dA = make_desc(A, 16, 1024, 1), dB = make_desc(B, 8192, 1024, 1);
          wg_fence();
#pragma unroll
          for (int k = 0; k < 4; k++) wgmma_n256_ss_tb(acc, dA + 2 * k, dB + 128 * k, (kb | k) != 0);
          wg_commit();
          if (prev >= 0) {
            wg_wait<1>();
            if (lane == 0) mbar_arrive_remote(bar_empty + 8 * prev, 0);
            if (lane == 1) mbar_arrive_remote(bar_empty + 8 * prev, 1);
          }
          prev = s;
          if (++s == G_STAGES) { s = 0; ph ^= 1; }
        }
        wg_wait<0>();
        if (lane == 0) mbar_arrive_remote(bar_empty + 8 * prev, 0);
        if (lane == 1) mbar_arrive_remote(bar_empty + 8 * prev, 1);
        fence_regs(acc);
        store_tile<4>(acc, t.scale, stg, &maps.out, t.out_col, t.row0, wg, wwarp, lane, tid_wg);
        if (MODE == 0) write_norms<8>(acc, t.scale, t.out_col >> 5, (t.row0 + wg * 64 + wwarp * 16) >> 4, lane);
      }
    } else {
      const int idx = (c - 64) * 2 + rank;
      for (int it = 0; it < 4; it++) {
        const int row0 = (idx * 4 + it) * 128;
        float acc[32];
        int prev = -1;
#pragma unroll 1
        for (int kb = 0; kb < 16; kb++) {
          mbar_wait(bar_full + 8 * s, ph);
          const uint32_t A = sbase + s * G_STAGE_BYTES + wg * 8192, B = sbase + s * G_STAGE_BYTES + 16384;
          const uint64_t dA = make_desc(A, 16, 1024, 1), dB = make_desc(B, 4096, 512, 2);
          wg_fence();
#pragma unroll
          for (int k = 0; k < 4; k++) wgmma_n64_ss_tb(acc, dA + 2 * k, dB + 64 * k, (kb | k) != 0);
          wg_commit();
          if (prev >= 0) {
            wg_wait<1>();
            if (lane == 0) mbar_arrive(bar_empty + 8 * prev);
          }
          prev = s;
          if (++s == G_STAGES) { s = 0; ph ^= 1; }
        }
        wg_wait<0>();
        if (lane == 0) mbar_arrive(bar_empty + 8 * prev);
        fence_regs(acc);
        store_tile<1>(acc, 1.0f, stg + (it & 1) * 8192, &maps.out, 4096, row0, wg, wwarp, lane, tid_wg);
        write_norms<2>(acc, 1.0f, 128, (row0 + wg * 64 + wwarp * 16) >> 4, lane);
      }
    }
    if (tid_wg == 0) bulk_wait<0>();
  }
  cluster_sync();
}

struct AttnMaps { CUtensorMap q, kv, o; };

constexpr int A_STAGES = 8;
constexpr int A_STAGE_BYTES = 16384;
constexpr int A_Q_OFF = A_STAGES * A_STAGE_BYTES;
constexpr int A_O_OFF = A_Q_OFF + 16384;
constexpr int A_ONES_OFF = A_O_OFF + 16384;
constexpr int A_BAR_OFF = A_ONES_OFF + 1024;
constexpr int A_SMEM = A_BAR_OFF + 256 + 1024;
constexpr int A_THREADS = 512;
constexpr int A_UNITS_PER_CTA = 4;
constexpr int A_PF = 3;

__device__ __forceinline__ float ex2_poly(float x) {
  const float magic = 12582912.0f;
  float t = x + magic;
  float f = x - (t - magic);
  float p = fmaf(f, 5.51716703e-02f, 2.42611125e-01f);
  p = fmaf(p, f, 6.93260985e-01f);
  p = fmaf(p, f, 9.99928073e-01f);
  return __uint_as_float(__float_as_uint(p) + (__float_as_uint(t) << 23));
}

#define POLY_MASK 0x2A55
#define PV_GROUPS 2
constexpr uint32_t DESC_HI = (512u >> 4) | (2u << 30);
constexpr uint32_t V_K_STEP = (1024u >> 4) - ((1024u >> 4) << 16);
constexpr uint32_t V_STAGE_STEP = (16384u >> 4) - ((16384u >> 4) << 16);
__device__ __forceinline__ uint64_t desc64(uint32_t lo, uint32_t hi) { return ((uint64_t)hi << 32) | lo; }

__device__ __forceinline__ void unit_coords(int u, int& q_col, int& k_col, int& v_col) {
  const int b = u >> 8, h = (u >> 3) & 31;
  q_col = b ? 3072 + h * 32 : h * 32; k_col = b ? 4096 : 1024 + h * 32; v_col = b ? 4128 : 2048 + h * 32;
}
__device__ __forceinline__ void issue_kv(const AttnMaps& maps, uint32_t sbase, int g) {
  const int s = g & (A_STAGES - 1);
  const uint32_t bar_full = sbase + A_BAR_OFF + 8 * s, bar_empty = bar_full + 8 * A_STAGES;
  int q_col, k_col, v_col;
  unit_coords(blockIdx.x * A_UNITS_PER_CTA + (g >> 4), q_col, k_col, v_col);
  if (g >= A_STAGES) mbar_wait(bar_empty, ((g >> 3) - 1) & 1);
  mbar_expect_tx(bar_full, A_STAGE_BYTES);
  tma_load_2d(sbase + s * A_STAGE_BYTES, &maps.kv, bar_full, k_col, (g & 15) * 128);
  tma_load_2d(sbase + s * A_STAGE_BYTES + 8192, &maps.kv, bar_full, v_col, (g & 15) * 128);
}
__device__ __forceinline__ void issue_q(const AttnMaps& maps, uint32_t sbase, int it) {
  const int u = blockIdx.x * A_UNITS_PER_CTA + it;
  const uint32_t bar_qfull = sbase + A_BAR_OFF + 16 * A_STAGES;
  int q_col, k_col, v_col;
  unit_coords(u, q_col, k_col, v_col);
  mbar_expect_tx(bar_qfull, 16384);
  tma_load_2d(sbase + A_Q_OFF, &maps.q, bar_qfull, q_col, (u & 7) * 256);
}

template <bool FAST>
__device__ __forceinline__ void attn_unit(const AttnMaps& maps, const uint32_t sbase, const int it, const int warp, const int lane) {
  const uint32_t bar_full = sbase + A_BAR_OFF, bar_empty = bar_full + 8 * A_STAGES;
  const uint32_t bar_qfull = bar_empty + 8 * A_STAGES, bar_qempty = bar_qfull + 8;
  const int wg = warp >> 2, wwarp = warp & 3;
  const bool issuer = (wwarp == wg) && (lane == 0);
  const uint32_t k_lo0 = (sbase >> 4) | (1u << 16);
  const uint32_t v_lo0 = ((sbase + 8192) >> 4) | (((A_ONES_OFF - 8192) >> 4) << 16);
  uint32_t qf[8];
  mbar_wait(bar_qfull, it & 1);
  {
    const int mi = lane >> 3;
    const int row = wg * 64 + wwarp * 16 + (lane & 7) + (mi & 1) * 8;
    const uint32_t rbase = sbase + A_Q_OFF + row * 64;
    const int sw = (row >> 1) & 3;
    ldmatrix_x4(rbase + (((mi >> 1) ^ sw) << 4), qf[0], qf[1], qf[2], qf[3]);
    ldmatrix_x4(rbase + (((2 + (mi >> 1)) ^ sw) << 4), qf[4], qf[5], qf[6], qf[7]);
  }
  __syncwarp();
  if (lane == 0) mbar_arrive(bar_qempty);

  float o[20];
#pragma unroll
  for (int i = 0; i < 20; i++) o[i] = 0.f;
  float m0 = -INFINITY, m1 = -INFINITY;

#pragma unroll 1
  for (int j = 0; j < 16; j++) {
    const int g = it * 16 + j, s = j & 7;
    if (issuer) {
      if ((j & 3) == wg && g + A_PF < 16 * A_UNITS_PER_CTA) issue_kv(maps, sbase, g + A_PF);
      if (j == 8 && wg == 0 && it + 1 < A_UNITS_PER_CTA) { mbar_wait(bar_qempty, it & 1); issue_q(maps, sbase, it + 1); }
    }
    __syncwarp();
    mbar_wait(bar_full + 8 * s, (j >> 3) & 1);
    const uint32_t k_lo = k_lo0 + s * (A_STAGE_BYTES >> 4), v_lo = v_lo0 + s * V_STAGE_STEP;
    if (FAST) {
      float sc[64];
      wg_fence();
      wgmma_n128_rs(sc, qf[0], qf[1], qf[2], qf[3], desc64(k_lo, DESC_HI), 0);
      wgmma_n128_rs(sc, qf[4], qf[5], qf[6], qf[7], desc64(k_lo + 2, DESC_HI), 1);
      wg_commit();
      wg_wait<0>();
      fence_regs(sc);
#pragma unroll
      for (int c = 0; c < PV_GROUPS; c++) {
        constexpr int KPG = 8 / PV_GROUPS;
        uint32_t p[4 * KPG];
#pragma unroll
        for (int i = 0; i < 4 * KPG; i++) {
          const int e = 2 * (c * 4 * KPG + i);
          const float e0 = ((POLY_MASK >> (e & 15)) & 1) ? ex2_poly(sc[e]) : ex2(sc[e]);
          const float e1 = ((POLY_MASK >> ((e + 1) & 15)) & 1) ? ex2_poly(sc[e + 1]) : ex2(sc[e + 1]);
          p[i] = pack_bf16(e0, e1);
        }
        wg_fence();
#pragma unroll
        for (int kk = 0; kk < KPG; kk++)
          wgmma_n40_rs_tb(o, p[4 * kk], p[4 * kk + 1], p[4 * kk + 2], p[4 * kk + 3],
                          desc64(v_lo + (c * KPG + kk) * V_K_STEP, DESC_HI), 1);
      }
      wg_commit();
      wg_wait<0>();
      fence_regs(o);
    } else {
#pragma unroll 1
      for (int hf = 0; hf < 2; hf++) {
        float sc[32];
        wg_fence();
        wgmma_n64_rs(sc, qf[0], qf[1], qf[2], qf[3], desc64(k_lo + hf * 256, DESC_HI), 0);
        wgmma_n64_rs(sc, qf[4], qf[5], qf[6], qf[7], desc64(k_lo + hf * 256 + 2, DESC_HI), 1);
        wg_commit();
        wg_wait<0>();
        fence_regs(sc);
        float n0 = m0, n1 = m1;
#pragma unroll
        for (int i = 0; i < 8; i++) {
          n0 = fmaxf(n0, fmaxf(sc[4 * i], sc[4 * i + 1]));
          n1 = fmaxf(n1, fmaxf(sc[4 * i + 2], sc[4 * i + 3]));
        }
        n0 = fmaxf(n0, __shfl_xor_sync(0xffffffffu, n0, 1)); n0 = fmaxf(n0, __shfl_xor_sync(0xffffffffu, n0, 2));
        n1 = fmaxf(n1, __shfl_xor_sync(0xffffffffu, n1, 1)); n1 = fmaxf(n1, __shfl_xor_sync(0xffffffffu, n1, 2));
        const float z0 = (n0 == -INFINITY) ? 0.f : n0, z1 = (n1 == -INFINITY) ? 0.f : n1;
        const float a0 = ex2(m0 - z0), a1 = ex2(m1 - z1);
        m0 = n0; m1 = n1;
#pragma unroll
        for (int i = 0; i < 5; i++) { o[4 * i] *= a0; o[4 * i + 1] *= a0; o[4 * i + 2] *= a1; o[4 * i + 3] *= a1; }
        uint32_t p[16];
#pragma unroll
        for (int i = 0; i < 8; i++) {
          p[2 * i] = pack_bf16(ex2(sc[4 * i] - z0), ex2(sc[4 * i + 1] - z0));
          p[2 * i + 1] = pack_bf16(ex2(sc[4 * i + 2] - z1), ex2(sc[4 * i + 3] - z1));
        }
        wg_fence();
#pragma unroll
        for (int kk = 0; kk < 4; kk++)
          wgmma_n40_rs_tb(o, p[4 * kk], p[4 * kk + 1], p[4 * kk + 2], p[4 * kk + 3],
                          desc64(v_lo + (hf * 4 + kk) * V_K_STEP, DESC_HI), 1);
        wg_commit();
        wg_wait<0>();
        fence_regs(o);
      }
    }
    if (lane == 0) mbar_arrive(bar_empty + 8 * s);
  }
  const float l0 = __shfl_sync(0xffffffffu, o[16], lane & ~3), l1 = __shfl_sync(0xffffffffu, o[18], lane & ~3);
  const float i0 = rcp(l0), i1 = rcp(l1);
  const uint32_t stg = sbase + A_O_OFF + wg * 4096;
  const bool leader = (wwarp == 0) && (lane == 0);
  if (leader) bulk_wait_read<0>();
  bar_sync(1 + wg, 128);
  {
    const int mi = lane >> 3;
    const int row = wwarp * 16 + (lane & 7) + (mi & 1) * 8;
    const int sw = (row >> 1) & 3;
#pragma unroll
    for (int jj = 0; jj < 2; jj++) {
      const int j = 2 * jj;
      stmatrix_x4(stg + row * 64 + (((2 * jj + (mi >> 1)) ^ sw) << 4),
                  pack_bf16(o[4 * j] * i0, o[4 * j + 1] * i0), pack_bf16(o[4 * j + 2] * i1, o[4 * j + 3] * i1),
                  pack_bf16(o[4 * j + 4] * i0, o[4 * j + 5] * i0), pack_bf16(o[4 * j + 6] * i1, o[4 * j + 7] * i1));
    }
  }
  fence_proxy_async();
  bar_sync(1 + wg, 128);
  if (leader) {
    const int u = blockIdx.x * A_UNITS_PER_CTA + it;
    tma_store_2d(&maps.o, stg, (u >> 8) * 1024 + ((u >> 3) & 31) * 32, (u & 7) * 256 + wg * 64);
    bulk_commit();
  }
}

__global__ void __launch_bounds__(A_THREADS, 1) attn_kernel(const __grid_constant__ AttnMaps maps) {
  extern __shared__ uint8_t smem_raw[];
  const uint32_t sbase = (smem_u32(smem_raw) + 1023u) & ~1023u;
  uint8_t* sgen = smem_raw + (sbase - smem_u32(smem_raw));
  const int tid = threadIdx.x, lane = tid & 31;
  const int warp = __shfl_sync(0xffffffffu, tid >> 5, 0);

  if (tid == 0) {
    const uint32_t bar = sbase + A_BAR_OFF;
    for (int s = 0; s < A_STAGES; s++) { mbar_init(bar + 8 * s, 1); mbar_init(bar + 8 * (A_STAGES + s), 16); }
    mbar_init(bar + 16 * A_STAGES, 1); mbar_init(bar + 16 * A_STAGES + 8, 16);
    fence_mbar_init();
  }
  if (tid >= 64 && tid < 128) {
    *reinterpret_cast<uint4*>(sgen + A_ONES_OFF + (tid - 64) * 16) = make_uint4(0x00003F80u, 0, 0, 0);
    fence_proxy_async();
  }
  if (tid == 128) { prefetch_tmap(&maps.q); prefetch_tmap(&maps.kv); prefetch_tmap(&maps.o); }
  __syncthreads();
  pdl_launch();
  pdl_wait();

  if (tid == 0) {
    issue_q(maps, sbase, 0);
    for (int g = 0; g < A_PF; g++) issue_kv(maps, sbase, g);
  }

#pragma unroll 1
  for (int it = 0; it < A_UNITS_PER_CTA; it++) {
    const int u = blockIdx.x * A_UNITS_PER_CTA + it;
    const int b = u >> 8, h = (u >> 3) & 31, qt = u & 7;
    const int qg = b ? 96 + h : h, kg = b ? 128 : 32 + h, vg = b ? 129 : 64 + h;
    const uint4 kn = *reinterpret_cast<const uint4*>(g_nrm + kg * 128 + lane * 4);
    const uint4 vn = *reinterpret_cast<const uint4*>(g_nrm + vg * 128 + lane * 4);
    const uint32_t qn = __float_as_uint(g_nrm[qg * 128 + qt * 16 + (warp >> 2) * 4 + (lane & 3)]);
    const float k2 = __uint_as_float(__reduce_max_sync(0xffffffffu, max(max(kn.x, kn.y), max(kn.z, kn.w))));
    const float v2 = __uint_as_float(__reduce_max_sync(0xffffffffu, max(max(vn.x, vn.y), max(vn.z, vn.w))));
    const float q2 = __uint_as_float(__reduce_max_sync(0xffffffffu, qn));
    const bool fast = (q2 * k2 <= 3600.0f) && (v2 <= 1.2e24f) && (v2 >= 8.3e-25f);
    if (fast) attn_unit<true>(maps, sbase, it, warp, lane);
    else attn_unit<false>(maps, sbase, it, warp, lane);
  }
  if ((tid & 127) == 0) bulk_wait<0>();
}

typedef CUresult (*EncodeFn)(CUtensorMap*, CUtensorMapDataType, cuuint32_t, void*, const cuuint64_t*, const cuuint64_t*,
                             const cuuint32_t*, const cuuint32_t*, CUtensorMapInterleave, CUtensorMapSwizzle,
                             CUtensorMapL2promotion, CUtensorMapFloatOOBfill);

void make_map(EncodeFn enc, CUtensorMap* m, const void* ptr, uint64_t cols, uint64_t rows, uint64_t ld, uint32_t box_c,
              uint32_t box_r, CUtensorMapSwizzle swz) {
  cuuint64_t dims[2] = {cols, rows};
  cuuint64_t strides[1] = {ld * 2};
  cuuint32_t box[2] = {box_c, box_r};
  cuuint32_t es[2] = {1, 1};
  enc(m, CU_TENSOR_MAP_DATA_TYPE_BFLOAT16, 2, const_cast<void*>(ptr), dims, strides, box, es, CU_TENSOR_MAP_INTERLEAVE_NONE,
      swz, CU_TENSOR_MAP_L2_PROMOTION_L2_256B, CU_TENSOR_MAP_FLOAT_OOB_FILL_NONE);
}

template <typename... Args>
void launch(void (*kern)(Args...), int grid, int block, int smem, bool pdl, Args... args) {
  cudaLaunchConfig_t cfg = {};
  cfg.gridDim = dim3(grid); cfg.blockDim = dim3(block); cfg.dynamicSmemBytes = smem; cfg.stream = cudaStreamPerThread;
  cudaLaunchAttribute at[1];
  at[0].id = cudaLaunchAttributeProgrammaticStreamSerialization;
  at[0].val.programmaticStreamSerializationAllowed = 1;
  cfg.attrs = at; cfg.numAttrs = pdl ? 1 : 0;
  cudaLaunchKernelEx(&cfg, kern, args...);
}

}

extern "C" void kernel_launch(void* const* d_in, const int* in_sizes, int n_in, void* d_out, int out_size) {
  static GemmMaps m1, m3;
  static AttnMaps m2;
  static void* cached[9] = {};
  bool same = true;
  for (int i = 0; i < 8; i++) same = same && cached[i] == d_in[i];
  same = same && cached[8] == d_out;
  if (!same) {
    void* fn = nullptr;
    cudaDriverEntryPointQueryResult qr;
    cudaGetDriverEntryPoint("cuTensorMapEncodeTiled", &fn, cudaEnableDefault, &qr);
    EncodeFn enc = (EncodeFn)fn;
    void *qkv, *o;
    cudaGetSymbolAddress(&qkv, g_qkv);
    cudaGetSymbolAddress(&o, g_o);
    const auto S128 = CU_TENSOR_MAP_SWIZZLE_128B, S64 = CU_TENSOR_MAP_SWIZZLE_64B;
    make_map(enc, &m1.a0, d_in[0], 1024, 2048, 1024, 64, 128, S128);
    make_map(enc, &m1.a1, d_in[3], 1024, 2048, 1024, 64, 128, S128);
    make_map(enc, &m1.w0, d_in[1], 3072, 1024, 3072, 64, 64, S128);
    make_map(enc, &m1.w1, d_in[4], 1024, 1024, 1024, 64, 64, S128);
    make_map(enc, &m1.w2, d_in[5], 32, 1024, 32, 32, 64, S64);
    make_map(enc, &m1.w3, d_in[6], 32, 1024, 32, 32, 64, S64);
    make_map(enc, &m1.out, qkv, QKV_LD, 2048, QKV_LD, 64, 64, S128);
    make_map(enc, &m2.q, qkv, QKV_LD, 2048, QKV_LD, 32, 256, S64);
    make_map(enc, &m2.kv, qkv, QKV_LD, 2048, QKV_LD, 32, 128, S64);
    make_map(enc, &m2.o, o, O_LD, 2048, O_LD, 32, 64, S64);
    make_map(enc, &m3.a0, o, O_LD, 2048, O_LD, 64, 128, S128);
    m3.a1 = m3.a0;
    make_map(enc, &m3.w0, d_in[2], 1024, 1024, 1024, 64, 64, S128);
    make_map(enc, &m3.w1, d_in[7], 1024, 1024, 1024, 64, 64, S128);
    m3.w2 = m3.w0; m3.w3 = m3.w0;
    make_map(enc, &m3.out, d_out, 2048, 2048, 2048, 64, 64, S128);
    cudaFuncSetAttribute(gemm_kernel<0>, cudaFuncAttributeMaxDynamicSharedMemorySize, G_SMEM);
    cudaFuncSetAttribute(gemm_kernel<1>, cudaFuncAttributeMaxDynamicSharedMemorySize, G_SMEM);
    cudaFuncSetAttribute(attn_kernel, cudaFuncAttributeMaxDynamicSharedMemorySize, A_SMEM);
    for (int i = 0; i < 8; i++) cached[i] = d_in[i];
    cached[8] = d_out;
  }
  launch(gemm_kernel<0>, 132, G_THREADS, G_SMEM, false, m1);
  launch(attn_kernel, 128, A_THREADS, A_SMEM, true, m2);
  launch(gemm_kernel<1>, 128, G_THREADS, G_SMEM, true, m3);
}
```

```cpp
#include <cuda_runtime.h>
#include <cuda_bf16.h>
#include <cuda.h>
#include <stdint.h>

namespace {

constexpr int SEQ = 2048;
constexpr int QKV_LD = 4160;
constexpr int O_LD = 2048;
constexpr int NHEADCOL = QKV_LD / 32;
constexpr float QSCALE = 0.17677669529663687f * 1.4426950408889634f;

#define HC 32
constexpr float VSCALE = HC > 0 ? 0.70703125f : 1.0f;

__device__ __align__(1024) __nv_bfloat16 g_qkv[SEQ * QKV_LD];
__device__ __align__(1024) __nv_bfloat16 g_o[SEQ * O_LD];
__device__ __align__(1024) uint4 g_part[132 * 4 * 7 * 128];
__device__ uint32_t g_epoch;
__device__ __align__(128) uint32_t g_k1flag[160];
__device__ __align__(16) float g_nrm[NHEADCOL * 128];

__device__ __forceinline__ uint32_t smem_u32(const void* p) { return (uint32_t)__cvta_generic_to_shared(p); }
__device__ __forceinline__ void mbar_init(uint32_t bar, uint32_t count) {
  asm volatile("mbarrier.init.shared::cta.b64 [%0], %1;" ::"r"(bar), "r"(count) : "memory");
}
__device__ __forceinline__ void mbar_expect_tx(uint32_t bar, uint32_t bytes) {
  asm volatile("mbarrier.arrive.expect_tx.shared::cta.b64 _, [%0], %1;" ::"r"(bar), "r"(bytes) : "memory");
}
__device__ __forceinline__ void mbar_arrive(uint32_t bar) {
  asm volatile("mbarrier.arrive.shared::cta.b64 _, [%0];" ::"r"(bar) : "memory");
}
__device__ __forceinline__ void mbar_arrive_remote(uint32_t bar, uint32_t cta) {
  asm volatile("{\n.reg .b32 ra;\nmapa.shared::cluster.u32 ra, %0, %1;\n"
               "mbarrier.arrive.shared::cluster.b64 _, [ra];\n}\n" ::"r"(bar), "r"(cta) : "memory");
}
__device__ __forceinline__ uint32_t mbar_try(uint32_t bar, uint32_t parity) {
  uint32_t ok;
  asm volatile("{\n.reg .pred p;\nmbarrier.try_wait.parity.shared::cta.b64 p, [%1], %2;\nselp.u32 %0, 1, 0, p;\n}\n"
               : "=r"(ok) : "r"(bar), "r"(parity) : "memory");
  return ok;
}
__device__ __forceinline__ void mbar_wait(uint32_t bar, uint32_t parity) {
  uint32_t n = 0;
#pragma unroll 1
  while (!mbar_try(bar, parity)) {
    if (++n > (1u << 24)) break;
  }
}
__device__ __forceinline__ void tma_load_2d(uint32_t dst, const CUtensorMap* map, uint32_t bar, int c0, int c1) {
  asm volatile("cp.async.bulk.tensor.2d.shared::cluster.global.mbarrier::complete_tx::bytes [%0], [%1, {%3, %4}], [%2];"
               ::"r"(dst), "l"(map), "r"(bar), "r"(c0), "r"(c1) : "memory");
}
__device__ __forceinline__ void tma_load_2d_mc(uint32_t dst, const CUtensorMap* map, uint32_t bar, int c0, int c1, uint16_t mask) {
  asm volatile("cp.async.bulk.tensor.2d.shared::cluster.global.mbarrier::complete_tx::bytes.multicast::cluster [%0], [%1, {%3, %4}], [%2], %5;"
               ::"r"(dst), "l"(map), "r"(bar), "r"(c0), "r"(c1), "h"(mask) : "memory");
}
__device__ __forceinline__ void tma_store_2d(const CUtensorMap* map, uint32_t src, int c0, int c1) {
  asm volatile("cp.async.bulk.tensor.2d.global.shared::cta.bulk_group [%0, {%2, %3}], [%1];"
               ::"l"(map), "r"(src), "r"(c0), "r"(c1) : "memory");
}
__device__ __forceinline__ void tma_store_3d(const CUtensorMap* map, uint32_t src, int c0, int c1, int c2) {
  asm volatile("cp.async.bulk.tensor.3d.global.shared::cta.bulk_group [%0, {%2, %3, %4}], [%1];"
               ::"l"(map), "r"(src), "r"(c0), "r"(c1), "r"(c2) : "memory");
}
__device__ __forceinline__ void bulk_commit() { asm volatile("cp.async.bulk.commit_group;" ::: "memory"); }
template <int N> __device__ __forceinline__ void bulk_wait_read() {
  asm volatile("cp.async.bulk.wait_group.read %0;" ::"n"(N) : "memory");
}
template <int N> __device__ __forceinline__ void bulk_wait() {
  asm volatile("cp.async.bulk.wait_group %0;" ::"n"(N) : "memory");
}
__device__ __forceinline__ void prefetch_tmap(const CUtensorMap* map) {
  asm volatile("prefetch.tensormap [%0];" ::"l"(map) : "memory");
}
__device__ __forceinline__ void fence_proxy_async() { asm volatile("fence.proxy.async.shared::cta;" ::: "memory"); }
__device__ __forceinline__ void fence_mbar_init() { asm volatile("fence.mbarrier_init.release.cluster;" ::: "memory"); }
__device__ __forceinline__ void cluster_sync() {
  asm volatile("barrier.cluster.arrive.relaxed.aligned;\nbarrier.cluster.wait.acquire.aligned;" ::: "memory");
}
__device__ __forceinline__ void bar_sync(int id, int n) { asm volatile("bar.sync %0, %1;" ::"r"(id), "r"(n) : "memory"); }
__device__ __forceinline__ void pdl_wait() { asm volatile("griddepcontrol.wait;" ::: "memory"); }
__device__ __forceinline__ void pdl_launch() { asm volatile("griddepcontrol.launch_dependents;" ::: "memory"); }
__device__ __forceinline__ void wg_fence() { asm volatile("wgmma.fence.sync.aligned;" ::: "memory"); }
__device__ __forceinline__ void wg_commit() { asm volatile("wgmma.commit_group.sync.aligned;" ::: "memory"); }
template <int N> __device__ __forceinline__ void wg_wait() {
  asm volatile("wgmma.wait_group.sync.aligned %0;" ::"n"(N) : "memory");
}
__device__ __forceinline__ void stmatrix_x4(uint32_t addr, uint32_t r0, uint32_t r1, uint32_t r2, uint32_t r3) {
  asm volatile("stmatrix.sync.aligned.m8n8.x4.shared.b16 [%0], {%1, %2, %3, %4};"
               ::"r"(addr), "r"(r0), "r"(r1), "r"(r2), "r"(r3) : "memory");
}
__device__ __forceinline__ void ldmatrix_x4(uint32_t addr, uint32_t& r0, uint32_t& r1, uint32_t& r2, uint32_t& r3) {
  asm volatile("ldmatrix.sync.aligned.m8n8.x4.shared.b16 {%0, %1, %2, %3}, [%4];"
               : "=r"(r0), "=r"(r1), "=r"(r2), "=r"(r3) : "r"(addr) : "memory");
}
__device__ __forceinline__ uint32_t pack_bf16(float lo, float hi) {
  uint32_t r;
  asm("cvt.rn.bf16x2.f32 %0, %1, %2;" : "=r"(r) : "f"(hi), "f"(lo));
  return r;
}
__device__ __forceinline__ uint32_t pack_f16(float lo, float hi) {
  uint32_t r;
  asm("cvt.rn.f16x2.f32 %0, %1, %2;" : "=r"(r) : "f"(hi), "f"(lo));
  return r;
}
__device__ __forceinline__ float ex2(float x) {
  float y;
  asm("ex2.approx.ftz.f32 %0, %1;" : "=f"(y) : "f"(x));
  return y;
}
__device__ __forceinline__ float rcp(float x) {
  float y;
  asm("rcp.approx.ftz.f32 %0, %1;" : "=f"(y) : "f"(x));
  return y;
}
__device__ __forceinline__ uint64_t make_desc(uint32_t addr, uint32_t lbo, uint32_t sbo, uint32_t swz) {
  return (uint64_t)((addr & 0x3FFFF) >> 4) | ((uint64_t)((lbo & 0x3FFFF) >> 4) << 16) | ((uint64_t)((sbo & 0x3FFFF) >> 4) << 32) |
         ((uint64_t)swz << 62);
}
template <int R> __device__ __forceinline__ void fence_regs(float (&d)[R]) {
#pragma unroll
  for (int i = 0; i < R; i++) asm volatile("" : "+f"(d[i])::"memory");
}

__device__ __forceinline__ void wgmma_n256_ss_tb(float (&d)[128], uint64_t descA, uint64_t descB, int scaleD) {
  asm volatile("{\n.reg .pred p;\nsetp.ne.b32 p, %130, 0;\n"
    "wgmma.mma_async.sync.aligned.m64n256k16.f32.bf16.bf16 "
    "{%0, %1, %2, %3, %4, %5, %6, %7, %8, %9, %10, %11, %12, %13, %14, %15, %16, %17, %18, %19, %20, %21, %22, %23, %24, %25, %26, %27, %28, %29, %30, %31, %32, %33, %34, %35, %36, %37, %38, %39, %40, %41, %42, %43, %44, %45, %46, %47, %48, %49, %50, %51, %52, %53, %54, %55, %56, %57, %58, %59, %60, %61, %62, %63, %64, %65, %66, %67, %68, %69, %70, %71, %72, %73, %74, %75, %76, %77, %78, %79, %80, %81, %82, %83, %84, %85, %86, %87, %88, %89, %90, %91, %92, %93, %94, %95, %96, %97, %98, %99, %100, %101, %102, %103, %104, %105, %106, %107, %108, %109, %110, %111, %112, %113, %114, %115, %116, %117, %118, %119, %120, %121, %122, %123, %124, %125, %126, %127}, "
    "%128, %129, p, 1, 1, 0, 1;\n}\n"
    : "+f"(d[0]), "+f"(d[1]), "+f"(d[2]), "+f"(d[3]), "+f"(d[4]), "+f"(d[5]), "+f"(d[6]), "+f"(d[7]), "+f"(d[8]), "+f"(d[9]), "+f"(d[10]), "+f"(d[11]), "+f"(d[12]), "+f"(d[13]), "+f"(d[14]), "+f"(d[15]), "+f"(d[16]), "+f"(d[17]), "+f"(d[18]), "+f"(d[19]), "+f"(d[20]), "+f"(d[21]), "+f"(d[22]), "+f"(d[23]), "+f"(d[24]), "+f"(d[25]), "+f"(d[26]), "+f"(d[27]), "+f"(d[28]), "+f"(d[29]), "+f"(d[30]), "+f"(d[31]), "+f"(d[32]), "+f"(d[33]), "+f"(d[34]), "+f"(d[35]), "+f"(d[36]), "+f"(d[37]), "+f"(d[38]), "+f"(d[39]), "+f"(d[40]), "+f"(d[41]), "+f"(d[42]), "+f"(d[43]), "+f"(d[44]), "+f"(d[45]), "+f"(d[46]), "+f"(d[47]), "+f"(d[48]), "+f"(d[49]), "+f"(d[50]), "+f"(d[51]), "+f"(d[52]), "+f"(d[53]), "+f"(d[54]), "+f"(d[55]), "+f"(d[56]), "+f"(d[57]), "+f"(d[58]), "+f"(d[59]), "+f"(d[60]), "+f"(d[61]), "+f"(d[62]), "+f"(d[63]), "+f"(d[64]), "+f"(d[65]), "+f"(d[66]), "+f"(d[67]), "+f"(d[68]), "+f"(d[69]), "+f"(d[70]), "+f"(d[71]), "+f"(d[72]), "+f"(d[73]), "+f"(d[74]), "+f"(d[75]), "+f"(d[76]), "+f"(d[77]), "+f"(d[78]), "+f"(d[79]), "+f"(d[80]), "+f"(d[81]), "+f"(d[82]), "+f"(d[83]), "+f"(d[84]), "+f"(d[85]), "+f"(d[86]), "+f"(d[87]), "+f"(d[88]), "+f"(d[89]), "+f"(d[90]), "+f"(d[91]), "+f"(d[92]), "+f"(d[93]), "+f"(d[94]), "+f"(d[95]), "+f"(d[96]), "+f"(d[97]), "+f"(d[98]), "+f"(d[99]), "+f"(d[100]), "+f"(d[101]), "+f"(d[102]), "+f"(d[103]), "+f"(d[104]), "+f"(d[105]), "+f"(d[106]), "+f"(d[107]), "+f"(d[108]), "+f"(d[109]), "+f"(d[110]), "+f"(d[111]), "+f"(d[112]), "+f"(d[113]), "+f"(d[114]), "+f"(d[115]), "+f"(d[116]), "+f"(d[117]), "+f"(d[118]), "+f"(d[119]), "+f"(d[120]), "+f"(d[121]), "+f"(d[122]), "+f"(d[123]), "+f"(d[124]), "+f"(d[125]), "+f"(d[126]), "+f"(d[127])
    : "l"(descA), "l"(descB), "r"(scaleD));
}
__device__ __forceinline__ void wgmma_n64_ss_tb(float (&d)[32], uint64_t descA, uint64_t descB, int scaleD) {
  asm volatile("{\n.reg .pred p;\nsetp.ne.b32 p, %34, 0;\n"
    "wgmma.mma_async.sync.aligned.m64n64k16.f32.bf16.bf16 "
    "{%0, %1, %2, %3, %4, %5, %6, %7, %8, %9, %10, %11, %12, %13, %14, %15, %16, %17, %18, %19, %20, %21, %22, %23, %24, %25, %26, %27, %28, %29, %30, %31}, "
    "%32, %33, p, 1, 1, 0, 1;\n}\n"
    : "+f"(d[0]), "+f"(d[1]), "+f"(d[2]), "+f"(d[3]), "+f"(d[4]), "+f"(d[5]), "+f"(d[6]), "+f"(d[7]), "+f"(d[8]), "+f"(d[9]), "+f"(d[10]), "+f"(d[11]), "+f"(d[12]), "+f"(d[13]), "+f"(d[14]), "+f"(d[15]), "+f"(d[16]), "+f"(d[17]), "+f"(d[18]), "+f"(d[19]), "+f"(d[20]), "+f"(d[21]), "+f"(d[22]), "+f"(d[23]), "+f"(d[24]), "+f"(d[25]), "+f"(d[26]), "+f"(d[27]), "+f"(d[28]), "+f"(d[29]), "+f"(d[30]), "+f"(d[31])
    : "l"(descA), "l"(descB), "r"(scaleD));
}
__device__ __forceinline__ void wgmma_n64_rs(float (&d)[32], uint32_t a0, uint32_t a1, uint32_t a2, uint32_t a3, uint64_t descB, int scaleD) {
  asm volatile("{\n.reg .pred p;\nsetp.ne.b32 p, %37, 0;\n"
    "wgmma.mma_async.sync.aligned.m64n64k16.f32.bf16.bf16 "
    "{%0, %1, %2, %3, %4, %5, %6, %7, %8, %9, %10, %11, %12, %13, %14, %15, %16, %17, %18, %19, %20, %21, %22, %23, %24, %25, %26, %27, %28, %29, %30, %31}, "
    "{%32, %33, %34, %35}, %36, p, 1, 1, 0;\n}\n"
    : "+f"(d[0]), "+f"(d[1]), "+f"(d[2]), "+f"(d[3]), "+f"(d[4]), "+f"(d[5]), "+f"(d[6]), "+f"(d[7]), "+f"(d[8]), "+f"(d[9]), "+f"(d[10]), "+f"(d[11]), "+f"(d[12]), "+f"(d[13]), "+f"(d[14]), "+f"(d[15]), "+f"(d[16]), "+f"(d[17]), "+f"(d[18]), "+f"(d[19]), "+f"(d[20]), "+f"(d[21]), "+f"(d[22]), "+f"(d[23]), "+f"(d[24]), "+f"(d[25]), "+f"(d[26]), "+f"(d[27]), "+f"(d[28]), "+f"(d[29]), "+f"(d[30]), "+f"(d[31])
    : "r"(a0), "r"(a1), "r"(a2), "r"(a3), "l"(descB), "r"(scaleD));
}
__device__ __forceinline__ void wgmma_n40_rs_tb(float (&d)[20], uint32_t a0, uint32_t a1, uint32_t a2, uint32_t a3, uint64_t descB, int scaleD) {
  asm volatile("{\n.reg .pred p;\nsetp.ne.b32 p, %25, 0;\n"
    "wgmma.mma_async.sync.aligned.m64n40k16.f32.bf16.bf16 "
    "{%0, %1, %2, %3, %4, %5, %6, %7, %8, %9, %10, %11, %12, %13, %14, %15, %16, %17, %18, %19}, "
    "{%20, %21, %22, %23}, %24, p, 1, 1, 1;\n}\n"
    : "+f"(d[0]), "+f"(d[1]), "+f"(d[2]), "+f"(d[3]), "+f"(d[4]), "+f"(d[5]), "+f"(d[6]), "+f"(d[7]), "+f"(d[8]), "+f"(d[9]), "+f"(d[10]), "+f"(d[11]), "+f"(d[12]), "+f"(d[13]), "+f"(d[14]), "+f"(d[15]), "+f"(d[16]), "+f"(d[17]), "+f"(d[18]), "+f"(d[19])
    : "r"(a0), "r"(a1), "r"(a2), "r"(a3), "l"(descB), "r"(scaleD));
}
__device__ __forceinline__ void wgmma_h128_rs(uint32_t (&d)[32], uint32_t a0, uint32_t a1, uint32_t a2, uint32_t a3, uint64_t descB, int scaleD) {
  asm volatile("{\n.reg .pred p;\nsetp.ne.b32 p, %37, 0;\n"
    "wgmma.mma_async.sync.aligned.m64n128k16.f16.f16.f16 "
    "{%0, %1, %2, %3, %4, %5, %6, %7, %8, %9, %10, %11, %12, %13, %14, %15, %16, %17, %18, %19, %20, %21, %22, %23, %24, %25, %26, %27, %28, %29, %30, %31}, "
    "{%32, %33, %34, %35}, %36, p, 1, 1, 0;\n}\n"
    : "+r"(d[0]), "+r"(d[1]), "+r"(d[2]), "+r"(d[3]), "+r"(d[4]), "+r"(d[5]), "+r"(d[6]), "+r"(d[7]), "+r"(d[8]), "+r"(d[9]), "+r"(d[10]), "+r"(d[11]), "+r"(d[12]), "+r"(d[13]), "+r"(d[14]), "+r"(d[15]), "+r"(d[16]), "+r"(d[17]), "+r"(d[18]), "+r"(d[19]), "+r"(d[20]), "+r"(d[21]), "+r"(d[22]), "+r"(d[23]), "+r"(d[24]), "+r"(d[25]), "+r"(d[26]), "+r"(d[27]), "+r"(d[28]), "+r"(d[29]), "+r"(d[30]), "+r"(d[31])
    : "r"(a0), "r"(a1), "r"(a2), "r"(a3), "l"(descB), "r"(scaleD));
}
__device__ __forceinline__ void wgmma_h40_rs_tb(uint32_t (&d)[10], uint32_t a0, uint32_t a1, uint32_t a2, uint32_t a3, uint64_t descB, int scaleD) {
  asm volatile("{\n.reg .pred p;\nsetp.ne.b32 p, %15, 0;\n"
    "wgmma.mma_async.sync.aligned.m64n40k16.f16.f16.f16 "
    "{%0, %1, %2, %3, %4, %5, %6, %7, %8, %9}, "
    "{%10, %11, %12, %13}, %14, p, 1, 1, 1;\n}\n"
    : "+r"(d[0]), "+r"(d[1]), "+r"(d[2]), "+r"(d[3]), "+r"(d[4]), "+r"(d[5]), "+r"(d[6]), "+r"(d[7]), "+r"(d[8]), "+r"(d[9])
    : "r"(a0), "r"(a1), "r"(a2), "r"(a3), "l"(descB), "r"(scaleD));
}
__device__ __forceinline__ void wgmma_f16in_f32(float (&d)[16], uint32_t a0, uint32_t a1, uint32_t a2, uint32_t a3, uint64_t descB, int scaleD) {
  asm volatile("{\n.reg .pred p;\nsetp.ne.b32 p, %21, 0;\n"
    "wgmma.mma_async.sync.aligned.m64n32k16.f32.f16.f16 "
    "{%0, %1, %2, %3, %4, %5, %6, %7, %8, %9, %10, %11, %12, %13, %14, %15}, "
    "{%16, %17, %18, %19}, %20, p, 1, 1, 0;\n}\n"
    : "+f"(d[0]), "+f"(d[1]), "+f"(d[2]), "+f"(d[3]), "+f"(d[4]), "+f"(d[5]), "+f"(d[6]), "+f"(d[7]), "+f"(d[8]), "+f"(d[9]), "+f"(d[10]), "+f"(d[11]), "+f"(d[12]), "+f"(d[13]), "+f"(d[14]), "+f"(d[15])
    : "r"(a0), "r"(a1), "r"(a2), "r"(a3), "l"(descB), "r"(scaleD));
}
__device__ __forceinline__ void wgmma_f16in_f16(uint32_t (&d)[24], uint32_t a0, uint32_t a1, uint32_t a2, uint32_t a3, uint64_t descB, int scaleD) {
  asm volatile("{\n.reg .pred p;\nsetp.ne.b32 p, %29, 0;\n"
    "wgmma.mma_async.sync.aligned.m64n96k16.f16.f16.f16 "
    "{%0, %1, %2, %3, %4, %5, %6, %7, %8, %9, %10, %11, %12, %13, %14, %15, %16, %17, %18, %19, %20, %21, %22, %23}, "
    "{%24, %25, %26, %27}, %28, p, 1, 1, 0;\n}\n"
    : "+r"(d[0]), "+r"(d[1]), "+r"(d[2]), "+r"(d[3]), "+r"(d[4]), "+r"(d[5]), "+r"(d[6]), "+r"(d[7]), "+r"(d[8]), "+r"(d[9]), "+r"(d[10]), "+r"(d[11]), "+r"(d[12]), "+r"(d[13]), "+r"(d[14]), "+r"(d[15]), "+r"(d[16]), "+r"(d[17]), "+r"(d[18]), "+r"(d[19]), "+r"(d[20]), "+r"(d[21]), "+r"(d[22]), "+r"(d[23])
    : "r"(a0), "r"(a1), "r"(a2), "r"(a3), "l"(descB), "r"(scaleD));
}
__device__ __forceinline__ void wgmma_f16in_f32(float (&d)[24], uint32_t a0, uint32_t a1, uint32_t a2, uint32_t a3, uint64_t descB, int scaleD) {
  asm volatile("{\n.reg .pred p;\nsetp.ne.b32 p, %29, 0;\n"
    "wgmma.mma_async.sync.aligned.m64n48k16.f32.f16.f16 "
    "{%0, %1, %2, %3, %4, %5, %6, %7, %8, %9, %10, %11, %12, %13, %14, %15, %16, %17, %18, %19, %20, %21, %22, %23}, "
    "{%24, %25, %26, %27}, %28, p, 1, 1, 0;\n}\n"
    : "+f"(d[0]), "+f"(d[1]), "+f"(d[2]), "+f"(d[3]), "+f"(d[4]), "+f"(d[5]), "+f"(d[6]), "+f"(d[7]), "+f"(d[8]), "+f"(d[9]), "+f"(d[10]), "+f"(d[11]), "+f"(d[12]), "+f"(d[13]), "+f"(d[14]), "+f"(d[15]), "+f"(d[16]), "+f"(d[17]), "+f"(d[18]), "+f"(d[19]), "+f"(d[20]), "+f"(d[21]), "+f"(d[22]), "+f"(d[23])
    : "r"(a0), "r"(a1), "r"(a2), "r"(a3), "l"(descB), "r"(scaleD));
}
__device__ __forceinline__ void wgmma_f16in_f16(uint32_t (&d)[20], uint32_t a0, uint32_t a1, uint32_t a2, uint32_t a3, uint64_t descB, int scaleD) {
  asm volatile("{\n.reg .pred p;\nsetp.ne.b32 p, %25, 0;\n"
    "wgmma.mma_async.sync.aligned.m64n80k16.f16.f16.f16 "
    "{%0, %1, %2, %3, %4, %5, %6, %7, %8, %9, %10, %11, %12, %13, %14, %15, %16, %17, %18, %19}, "
    "{%20, %21, %22, %23}, %24, p, 1, 1, 0;\n}\n"
    : "+r"(d[0]), "+r"(d[1]), "+r"(d[2]), "+r"(d[3]), "+r"(d[4]), "+r"(d[5]), "+r"(d[6]), "+r"(d[7]), "+r"(d[8]), "+r"(d[9]), "+r"(d[10]), "+r"(d[11]), "+r"(d[12]), "+r"(d[13]), "+r"(d[14]), "+r"(d[15]), "+r"(d[16]), "+r"(d[17]), "+r"(d[18]), "+r"(d[19])
    : "r"(a0), "r"(a1), "r"(a2), "r"(a3), "l"(descB), "r"(scaleD));
}
__device__ __forceinline__ void wgmma_n256_ss_tb2(float (&d0)[64], float (&d1)[64], uint64_t descA, uint64_t descB, int scaleD) {
  asm volatile("{\n.reg .pred p;\nsetp.ne.b32 p, %130, 0;\n"
    "wgmma.mma_async.sync.aligned.m64n256k16.f32.bf16.bf16 "
    "{%0, %1, %2, %3, %4, %5, %6, %7, %8, %9, %10, %11, %12, %13, %14, %15, %16, %17, %18, %19, %20, %21, %22, %23, %24, %25, %26, %27, %28, %29, %30, %31, %32, %33, %34, %35, %36, %37, %38, %39, %40, %41, %42, %43, %44, %45, %46, %47, %48, %49, %50, %51, %52, %53, %54, %55, %56, %57, %58, %59, %60, %61, %62, %63, %64, %65, %66, %67, %68, %69, %70, %71, %72, %73, %74, %75, %76, %77, %78, %79, %80, %81, %82, %83, %84, %85, %86, %87, %88, %89, %90, %91, %92, %93, %94, %95, %96, %97, %98, %99, %100, %101, %102, %103, %104, %105, %106, %107, %108, %109, %110, %111, %112, %113, %114, %115, %116, %117, %118, %119, %120, %121, %122, %123, %124, %125, %126, %127}, "
    "%128, %129, p, 1, 1, 0, 1;\n}\n"
    : "+f"(d0[0]), "+f"(d0[1]), "+f"(d0[2]), "+f"(d0[3]), "+f"(d0[4]), "+f"(d0[5]), "+f"(d0[6]), "+f"(d0[7]), "+f"(d0[8]), "+f"(d0[9]), "+f"(d0[10]), "+f"(d0[11]), "+f"(d0[12]), "+f"(d0[13]), "+f"(d0[14]), "+f"(d0[15]), "+f"(d0[16]), "+f"(d0[17]), "+f"(d0[18]), "+f"(d0[19]), "+f"(d0[20]), "+f"(d0[21]), "+f"(d0[22]), "+f"(d0[23]), "+f"(d0[24]), "+f"(d0[25]), "+f"(d0[26]), "+f"(d0[27]), "+f"(d0[28]), "+f"(d0[29]), "+f"(d0[30]), "+f"(d0[31]), "+f"(d0[32]), "+f"(d0[33]), "+f"(d0[34]), "+f"(d0[35]), "+f"(d0[36]), "+f"(d0[37]), "+f"(d0[38]), "+f"(d0[39]), "+f"(d0[40]), "+f"(d0[41]), "+f"(d0[42]), "+f"(d0[43]), "+f"(d0[44]), "+f"(d0[45]), "+f"(d0[46]), "+f"(d0[47]), "+f"(d0[48]), "+f"(d0[49]), "+f"(d0[50]), "+f"(d0[51]), "+f"(d0[52]), "+f"(d0[53]), "+f"(d0[54]), "+f"(d0[55]), "+f"(d0[56]), "+f"(d0[57]), "+f"(d0[58]), "+f"(d0[59]), "+f"(d0[60]), "+f"(d0[61]), "+f"(d0[62]), "+f"(d0[63]), "+f"(d1[0]), "+f"(d1[1]), "+f"(d1[2]), "+f"(d1[3]), "+f"(d1[4]), "+f"(d1[5]), "+f"(d1[6]), "+f"(d1[7]), "+f"(d1[8]), "+f"(d1[9]), "+f"(d1[10]), "+f"(d1[11]), "+f"(d1[12]), "+f"(d1[13]), "+f"(d1[14]), "+f"(d1[15]), "+f"(d1[16]), "+f"(d1[17]), "+f"(d1[18]), "+f"(d1[19]), "+f"(d1[20]), "+f"(d1[21]), "+f"(d1[22]), "+f"(d1[23]), "+f"(d1[24]), "+f"(d1[25]), "+f"(d1[26]), "+f"(d1[27]), "+f"(d1[28]), "+f"(d1[29]), "+f"(d1[30]), "+f"(d1[31]), "+f"(d1[32]), "+f"(d1[33]), "+f"(d1[34]), "+f"(d1[35]), "+f"(d1[36]), "+f"(d1[37]), "+f"(d1[38]), "+f"(d1[39]), "+f"(d1[40]), "+f"(d1[41]), "+f"(d1[42]), "+f"(d1[43]), "+f"(d1[44]), "+f"(d1[45]), "+f"(d1[46]), "+f"(d1[47]), "+f"(d1[48]), "+f"(d1[49]), "+f"(d1[50]), "+f"(d1[51]), "+f"(d1[52]), "+f"(d1[53]), "+f"(d1[54]), "+f"(d1[55]), "+f"(d1[56]), "+f"(d1[57]), "+f"(d1[58]), "+f"(d1[59]), "+f"(d1[60]), "+f"(d1[61]), "+f"(d1[62]), "+f"(d1[63])
    : "l"(descA), "l"(descB), "r"(scaleD));
}
__device__ __forceinline__ void wgmma_n128_ss_tb(float (&d)[64], uint64_t descA, uint64_t descB, int scaleD) {
  asm volatile("{\n.reg .pred p;\nsetp.ne.b32 p, %66, 0;\n"
    "wgmma.mma_async.sync.aligned.m64n128k16.f32.bf16.bf16 "
    "{%0, %1, %2, %3, %4, %5, %6, %7, %8, %9, %10, %11, %12, %13, %14, %15, %16, %17, %18, %19, %20, %21, %22, %23, %24, %25, %26, %27, %28, %29, %30, %31, %32, %33, %34, %35, %36, %37, %38, %39, %40, %41, %42, %43, %44, %45, %46, %47, %48, %49, %50, %51, %52, %53, %54, %55, %56, %57, %58, %59, %60, %61, %62, %63}, "
    "%64, %65, p, 1, 1, 0, 1;\n}\n"
    : "+f"(d[0]), "+f"(d[1]), "+f"(d[2]), "+f"(d[3]), "+f"(d[4]), "+f"(d[5]), "+f"(d[6]), "+f"(d[7]), "+f"(d[8]), "+f"(d[9]), "+f"(d[10]), "+f"(d[11]), "+f"(d[12]), "+f"(d[13]), "+f"(d[14]), "+f"(d[15]), "+f"(d[16]), "+f"(d[17]), "+f"(d[18]), "+f"(d[19]), "+f"(d[20]), "+f"(d[21]), "+f"(d[22]), "+f"(d[23]), "+f"(d[24]), "+f"(d[25]), "+f"(d[26]), "+f"(d[27]), "+f"(d[28]), "+f"(d[29]), "+f"(d[30]), "+f"(d[31]), "+f"(d[32]), "+f"(d[33]), "+f"(d[34]), "+f"(d[35]), "+f"(d[36]), "+f"(d[37]), "+f"(d[38]), "+f"(d[39]), "+f"(d[40]), "+f"(d[41]), "+f"(d[42]), "+f"(d[43]), "+f"(d[44]), "+f"(d[45]), "+f"(d[46]), "+f"(d[47]), "+f"(d[48]), "+f"(d[49]), "+f"(d[50]), "+f"(d[51]), "+f"(d[52]), "+f"(d[53]), "+f"(d[54]), "+f"(d[55]), "+f"(d[56]), "+f"(d[57]), "+f"(d[58]), "+f"(d[59]), "+f"(d[60]), "+f"(d[61]), "+f"(d[62]), "+f"(d[63])
    : "l"(descA), "l"(descB), "r"(scaleD));
}
#define Q_RAW 1
struct GemmMaps {
  CUtensorMap a0, a1, w0, w1, w2, w3, out, outc;
};

constexpr int G_STAGES = 4;
constexpr int G_STAGE_BYTES = 49152;
constexpr int G_STG_OFF = G_STAGES * G_STAGE_BYTES;
constexpr int G_BAR_OFF = G_STG_OFF + 32768;
constexpr int G_SMEM = G_BAR_OFF + 128 + 1024;
constexpr int S_STAGE_BYTES = 73728;
#define QDONE_KB 6
constexpr int G_THREADS = 384;

struct Tile { const CUtensorMap* a; const CUtensorMap* w; int a_k0, row0, w_col, out_col; bool is_k, is_v; };

template <int MODE>
__device__ __forceinline__ Tile get_tile(const GemmMaps& m, int c, int rank, int it) {
  Tile t;
  t.is_k = t.is_v = false;
  t.row0 = (c & 7) * 256 + rank * 128;
  t.a_k0 = 0;
  if (MODE == 0) {
    if (it == 0 && c >= 32) {
      const int nt = (c - 32) >> 3;
      t.a = &m.a1; t.w = &m.w1; t.w_col = nt * 256; t.out_col = 3072 + nt * 256;
    } else {
      const int nt = it * 4 + (c >> 3);
      t.a = &m.a0; t.w = &m.w0; t.w_col = nt * 256; t.out_col = nt * 256;
      t.is_k = it == 1 && c < 32; t.is_v = it == 1 && c >= 32;
    }
  } else {
    const int b = c >> 5, nt = (c & 31) >> 3;
    t.a = &m.a0; t.w = b ? &m.w1 : &m.w0; t.a_k0 = b * 1024; t.w_col = nt * 256; t.out_col = b * 1024 + nt * 256;
  }
  return t;
}

__device__ __forceinline__ void tma_load_w(uint32_t dst, const CUtensorMap* map, uint32_t bar, int k0, int chunk) {
  asm volatile("cp.async.bulk.tensor.3d.shared::cluster.global.mbarrier::complete_tx::bytes [%0], [%1, {%3, %4, %5}], [%2];"
               ::"r"(dst), "l"(map), "r"(bar), "r"(0), "r"(k0), "r"(chunk) : "memory");
}
__device__ __forceinline__ void tma_load_w_mc(uint32_t dst, const CUtensorMap* map, uint32_t bar, int k0, int chunk) {
  asm volatile("cp.async.bulk.tensor.3d.shared::cluster.global.mbarrier::complete_tx::bytes.multicast::cluster [%0], [%1, {%3, %4, %5}], [%2], %6;"
               ::"r"(dst), "l"(map), "r"(bar), "r"(0), "r"(k0), "r"(chunk), "h"((uint16_t)3) : "memory");
}
__host__ __device__ constexpr int hbit(int g) { return ((g >> 1) & 1) | ((g & 1) << 1); }
template <bool KEYS>
__device__ __forceinline__ uint32_t norm_reduce4(float (&a)[4], float (&b)[4], float scale, int colgroup0, int rowblock, int lane) {
  const bool b0 = lane & 1, b1 = lane & 2;
#pragma unroll
  for (int i = 0; i < 2; i++) {
    a[i] = (b0 ? a[i + 2] : a[i]) + __shfl_xor_sync(0xffffffffu, b0 ? a[i] : a[i + 2], 1);
    b[i] = (b0 ? b[i + 2] : b[i]) + __shfl_xor_sync(0xffffffffu, b0 ? b[i] : b[i + 2], 1);
  }
  a[0] = (b1 ? a[1] : a[0]) + __shfl_xor_sync(0xffffffffu, b1 ? a[0] : a[1], 2);
  b[0] = (b1 ? b[1] : b[0]) + __shfl_xor_sync(0xffffffffu, b1 ? b[0] : b[1], 2);
  const uint32_t u0 = __float_as_uint(a[0]) & 0x7fffffffu, u1 = __float_as_uint(b[0]) & 0x7fffffffu;
  uint32_t umax = max(u0, u1), hmask = 0;
#pragma unroll
  for (int o = 4; o < 32; o *= 2) umax = max(umax, __shfl_xor_sync(0xffffffffu, umax, o));
  uint32_t out = __float_as_uint(__uint_as_float(umax) * scale * scale) & 0x7fffffffu;
  if (KEYS) {
    uint32_t umin = min(u0, u1);
#pragma unroll
    for (int o = 4; o < 32; o *= 2) umin = min(umin, __shfl_xor_sync(0xffffffffu, umin, o));
    const bool h = umin >= 0x33800000u && umax <= 0x49800000u;
    hmask = __ballot_sync(0xffffffffu, h);
    out |= h ? 0u : 0x80000000u;
  }
  const int g = ((lane & 1) << 1) | ((lane >> 1) & 1);
  if (lane < 4) g_nrm[(colgroup0 + g) * 128 + rowblock] = __uint_as_float(out);
  return hmask;
}
template <bool KEYS, int H>
__device__ __forceinline__ uint32_t write_norms4(const float (&acc)[128], float scale, int colgroup0, int rowblock, int lane) {
  float a[4], b[4];
#pragma unroll
  for (int hh = 0; hh < 4; hh++) {
    float s0 = 0.f, s1 = 0.f;
#pragma unroll
    for (int j = 16 * H + 4 * hh; j < 16 * H + 4 * hh + 4; j++) {
      s0 = fmaf(acc[4 * j], acc[4 * j], s0); s0 = fmaf(acc[4 * j + 1], acc[4 * j + 1], s0);
      s1 = fmaf(acc[4 * j + 2], acc[4 * j + 2], s1); s1 = fmaf(acc[4 * j + 3], acc[4 * j + 3], s1);
    }
    a[hh] = s0; b[hh] = s1;
  }
  return norm_reduce4<KEYS>(a, b, scale, colgroup0, rowblock, lane);
}
template <int H>
__device__ __forceinline__ void write_norms4_packed(const uint32_t (&p)[64], int colgroup0, int rowblock, int lane) {
  float a[4], b[4];
#pragma unroll
  for (int hh = 0; hh < 4; hh++) {
    float s0 = 0.f, s1 = 0.f;
#pragma unroll
    for (int j = 16 * H + 4 * hh; j < 16 * H + 4 * hh + 4; j++) {
      const float l0 = __uint_as_float(p[2 * j] << 16), h0 = __uint_as_float(p[2 * j]);
      const float l1 = __uint_as_float(p[2 * j + 1] << 16), h1 = __uint_as_float(p[2 * j + 1]);
      s0 = fmaf(l0, l0, s0); s0 = fmaf(h0, h0, s0);
      s1 = fmaf(l1, l1, s1); s1 = fmaf(h1, h1, s1);
    }
    a[hh] = s0; b[hh] = s1;
  }
  norm_reduce4<false>(a, b, 1.0f, colgroup0, rowblock, lane);
}
__device__ __forceinline__ uint32_t write_norms2(const float (&acc)[32], int colgroup0, int rowblock, int lane) {
  uint32_t hmask = 0;
#pragma unroll
  for (int hh = 0; hh < 2; hh++) {
    float s0 = 0.f, s1 = 0.f;
#pragma unroll
    for (int j = 4 * hh; j < 4 * hh + 4; j++) {
      s0 = fmaf(acc[4 * j], acc[4 * j], s0); s0 = fmaf(acc[4 * j + 1], acc[4 * j + 1], s0);
      s1 = fmaf(acc[4 * j + 2], acc[4 * j + 2], s1); s1 = fmaf(acc[4 * j + 3], acc[4 * j + 3], s1);
    }
    s0 += __shfl_xor_sync(0xffffffffu, s0, 1); s1 += __shfl_xor_sync(0xffffffffu, s1, 1);
    s0 += __shfl_xor_sync(0xffffffffu, s0, 2); s1 += __shfl_xor_sync(0xffffffffu, s1, 2);
    const uint32_t u0 = __float_as_uint(s0) & 0x7fffffffu, u1 = __float_as_uint(s1) & 0x7fffffffu;
    uint32_t out = __reduce_max_sync(0xffffffffu, max(u0, u1));
    if (hh == 0) {
      const uint32_t umin = __reduce_min_sync(0xffffffffu, min(u0, u1));
      const bool h = umin >= 0x33800000u && out <= 0x49800000u;
      hmask = h ? 1u << hbit(0) : 0u;
      out |= h ? 0u : 0x80000000u;
    }
    if (lane == 0) g_nrm[(colgroup0 + hh) * 128 + rowblock] = __uint_as_float(out);
  }
  return hmask;
}

__device__ __forceinline__ uint32_t stg_addr(uint32_t buf, int q, int jj, int lane) {
  const int mi = lane >> 3, r = (lane & 7) + (mi & 1) * 8;
  return buf + q * 2048 + r * 128 + (((2 * jj + (mi >> 1)) ^ (r & 7)) << 4);
}
template <int NQ>
__device__ __forceinline__ void stg_store(uint32_t buf, const GemmMaps& maps, int col, int row, int lane) {
  fence_proxy_async();
  __syncwarp();
  if (lane == 0) {
    if (NQ == 1) tma_store_2d(&maps.outc, buf, col, row);
    else tma_store_3d(&maps.out, buf, 0, row, col >> 6);
    bulk_commit();
  }
}
template <int Q0, int NQ, bool SCALE, bool KEYS, int R>
__device__ __forceinline__ void store_tile(const float (&acc)[R], float scale, uint32_t hmask, uint32_t buf, const GemmMaps& maps,
                                           int col, int row, int lane) {
#pragma unroll
  for (int q = 0; q < NQ; q++) {
#pragma unroll
    for (int jj = 0; jj < 4; jj++) {
      const int j = 8 * (Q0 + q) + 2 * jj;
      uint32_t v[4];
      if (KEYS && ((hmask >> hbit((2 * (Q0 + q) + (jj >> 1)) & 3)) & 1)) {
#pragma unroll
        for (int i = 0; i < 4; i++) v[i] = pack_f16(acc[4 * j + 2 * i], acc[4 * j + 2 * i + 1]);
      } else {
#pragma unroll
        for (int i = 0; i < 4; i++)
          v[i] = (SCALE && (!KEYS || jj >= 2)) ? pack_bf16(acc[4 * j + 2 * i] * scale, acc[4 * j + 2 * i + 1] * scale)
                                               : pack_bf16(acc[4 * j + 2 * i], acc[4 * j + 2 * i + 1]);
      }
      stmatrix_x4(stg_addr(buf, q, jj, lane), v[0], v[1], v[2], v[3]);
    }
  }
  stg_store<NQ>(buf, maps, col, row, lane);
}
template <int H>
__device__ __forceinline__ void store_packed(const uint32_t (&p)[64], uint32_t buf, const GemmMaps& maps, int col, int row, int lane) {
#pragma unroll
  for (int q = 0; q < 2; q++)
#pragma unroll
    for (int jj = 0; jj < 4; jj++) {
      const int j = 8 * (2 * H + q) + 2 * jj;
      stmatrix_x4(stg_addr(buf, q, jj, lane), p[2 * j], p[2 * j + 1], p[2 * j + 2], p[2 * j + 3]);
    }
  stg_store<2>(buf, maps, col, row, lane);
}

#define GT(k) do {} while (0)
#define GTW(k) do {} while (0)
#define GTG(k) do {} while (0)

struct GCtx {
  uint32_t sbase, bar_full, bar_empty, stg;
  int tmode;
  int wg, wrow, lane;
  __device__ __forceinline__ void full(int kb) const { mbar_wait(bar_full + 8 * (kb & 3), (kb >> 2) & 1); }
  __device__ __forceinline__ void release(int kb) const {
    if (lane < 2) mbar_arrive_remote(bar_empty + 8 * (kb & 3), lane);
  }
  __device__ __forceinline__ uint64_t da(int kb) const { return make_desc(sbase + (kb & 3) * G_STAGE_BYTES + wg * 8192, 16, 1024, 1); }
  __device__ __forceinline__ uint64_t db(int kb) const { return make_desc(sbase + (kb & 3) * G_STAGE_BYTES + 16384, 8192, 1024, 1); }
  __device__ __forceinline__ void mma(float (&acc)[128], int kb) const {
    full(kb);
    const uint64_t dA = da(kb), dB = db(kb);
    wg_fence();
#pragma unroll
    for (int k = 0; k < 4; k++) wgmma_n256_ss_tb(acc, dA + 2 * k, dB + 128 * k, kb | k);
    wg_commit();
  }
  __device__ __forceinline__ void step(float (&acc)[128], int kb) const {
    mma(acc, kb);
    wg_wait<1>();
    release(kb - 1);
  }
  __device__ __forceinline__ void stg_free() const {
    if (lane == 0) bulk_wait_read<0>();
    __syncwarp();
  }
};

#define SKEW0 13
__device__ __forceinline__ void skewed_tail(float (&acc)[128], const GCtx& x) {
  if (x.wg == 1) {
    wg_wait<0>();
    bar_sync(7, 256);
  }
#pragma unroll 1
  for (int kb = SKEW0; kb < 16; kb++) x.step(acc, kb);
  if (x.wg == 0) asm volatile("bar.arrive 7, 256;" ::: "memory");
  wg_wait<0>();
  fence_regs(acc);
}
#define NQL 1
template <int MODE, int H>
__device__ __forceinline__ void last_half(const float (&acc)[128], const Tile& t, uint32_t buf, const GCtx& x, const GemmMaps& maps) {
  const int orow = t.row0 + x.wrow, col = t.out_col + H * 128;
  if (MODE == 0 && t.is_k) {
    const uint32_t hmask = write_norms4<true, H>(acc, 1.0f, col >> 5, orow >> 4, x.lane);
    if (NQL == 2) store_tile<2 * H, 2, false, true>(acc, 1.0f, hmask, buf, maps, col, orow, x.lane);
    else {
      store_tile<2 * H, 1, false, true>(acc, 1.0f, hmask, buf, maps, col, orow, x.lane);
      store_tile<2 * H + 1, 1, false, true>(acc, 1.0f, hmask, buf + 2048, maps, col + 64, orow, x.lane);
    }
  } else if (MODE == 0) {
    const float sc = x.wrow >= HC ? VSCALE : 1.0f;
    if (NQL == 2) store_tile<2 * H, 2, true, false>(acc, sc, 0, buf, maps, col, orow, x.lane);
    else {
      store_tile<2 * H, 1, true, false>(acc, sc, 0, buf, maps, col, orow, x.lane);
      store_tile<2 * H + 1, 1, true, false>(acc, sc, 0, buf + 2048, maps, col + 64, orow, x.lane);
    }
  } else {
    if (NQL == 2) store_tile<2 * H, 2, false, false>(acc, 1.0f, 0, buf, maps, col, orow, x.lane);
    else {
      store_tile<2 * H, 1, false, false>(acc, 1.0f, 0, buf, maps, col, orow, x.lane);
      store_tile<2 * H + 1, 1, false, false>(acc, 1.0f, 0, buf + 2048, maps, col + 64, orow, x.lane);
    }
  }
}
template <int MODE>
__device__ __forceinline__ void last_epilogue(const float (&acc)[128], const Tile& t, const GCtx& x, const GemmMaps& maps) {
  if (MODE == 0) x.stg_free();
  last_half<MODE, 0>(acc, t, x.stg, x, maps);
  mbar_wait(x.bar_empty, 1);
  last_half<MODE, 1>(acc, t, x.sbase + (x.stg - x.sbase - G_STG_OFF), x, maps);
  if (MODE == 0 && t.is_v) {
    const int orow = t.row0 + x.wrow;
    const float sc = x.wrow >= HC ? VSCALE : 1.0f;
    write_norms4<false, 0>(acc, sc, t.out_col >> 5, orow >> 4, x.lane);
    write_norms4<false, 1>(acc, sc, (t.out_col >> 5) + 4, orow >> 4, x.lane);
  }
}

__device__ __forceinline__ void small_load(const GemmMaps& maps, uint32_t sbase, uint32_t bar_full, int idx, int s, int kb) {
  mbar_expect_tx(bar_full + 8 * s, S_STAGE_BYTES);
  const uint32_t st = sbase + s * S_STAGE_BYTES;
  for (int it = 0; it < 4; it++) tma_load_2d(st + it * 16384, &maps.a1, bar_full + 8 * s, kb * 64, (idx * 4 + it) * 128);
  tma_load_2d(st + 65536, &maps.w2, bar_full + 8 * s, 0, kb * 64);
  tma_load_2d(st + 65536 + 4096, &maps.w3, bar_full + 8 * s, 0, kb * 64);
}

template <int MODE>
__global__ void __cluster_dims__(2, 1, 1) __launch_bounds__(G_THREADS, 1) gemm_kernel(const __grid_constant__ GemmMaps maps) {
  extern __shared__ uint8_t smem_raw[];
  const uint32_t sbase = (smem_u32(smem_raw) + 1023u) & ~1023u;
  const uint32_t bar_full = sbase + G_BAR_OFF, bar_empty = bar_full + 8 * G_STAGES;
  const int tid = threadIdx.x, lane = tid & 31;
  const int warp = __shfl_sync(0xffffffffu, tid >> 5, 0);
  const int c = blockIdx.x >> 1, rank = blockIdx.x & 1;
  const bool small = (MODE == 0) && (c >= 64);
  const int ntiles = MODE == 1 ? 1 : 2;
  GTG(14); GT(0);

  if (tid == 256) {
    for (int s = 0; s < G_STAGES; s++) { mbar_init(bar_full + 8 * s, 1); mbar_init(bar_empty + 8 * s, small ? 8 : 16); }
    mbar_init(bar_empty + 8 * G_STAGES, 8);
    fence_mbar_init();
    fence_proxy_async();
    if (!small) {
      const Tile t = get_tile<MODE>(maps, c, rank, 0);
      for (int kb = 0; kb < G_STAGES; kb++) {
        mbar_expect_tx(bar_full + 8 * kb, G_STAGE_BYTES);
        const uint32_t A = sbase + kb * G_STAGE_BYTES;
        if (MODE == 0) tma_load_2d(A, t.a, bar_full + 8 * kb, kb * 64, t.row0);
        tma_load_w(A + 16384, t.w, bar_full + 8 * kb, kb * 64, t.w_col >> 6);
        tma_load_w(A + 32768, t.w, bar_full + 8 * kb, kb * 64, (t.w_col >> 6) + 2);
      }
    } else {
      for (int kb = 0; kb < 3; kb++) small_load(maps, sbase, bar_full, (c - 64) * 2 + rank, kb, kb);
    }
  }
  if (tid == 288) {
    prefetch_tmap(&maps.out); prefetch_tmap(&maps.outc); prefetch_tmap(&maps.a0);
    if (MODE == 0) prefetch_tmap(&maps.w0);
  }
  cluster_sync();
  pdl_launch();
  GT(1);

  if (warp >= 8) {
    asm volatile("setmaxnreg.dec.sync.aligned.u32 40;");
    if (tid == 256) {
      if (!small) {
        for (int it = 0; it < ntiles; it++) {
          const Tile t = get_tile<MODE>(maps, c, rank, it);
          if (MODE == 1) {
            pdl_wait();
            if (blockIdx.x == 0) g_epoch = g_epoch + 1;
            for (int kb = 0; kb < G_STAGES; kb++)
              tma_load_2d(sbase + kb * G_STAGE_BYTES, t.a, bar_full + 8 * kb, t.a_k0 + kb * 64, t.row0);
          }
          const int kb0 = it == 0 ? G_STAGES : 0;
          for (int kb = kb0; kb < 16; kb++) {
            const int s = kb & 3;
            mbar_wait(bar_empty + 8 * s, ((kb >> 2) & 1) ^ 1);
            mbar_expect_tx(bar_full + 8 * s, G_STAGE_BYTES);
            const uint32_t A = sbase + s * G_STAGE_BYTES, B = A + 16384;
            tma_load_2d(A, t.a, bar_full + 8 * s, t.a_k0 + kb * 64, t.row0);
            tma_load_w_mc(B + rank * 16384, t.w, bar_full + 8 * s, kb * 64, (t.w_col >> 6) + 2 * rank);
          }
        }
      } else {
        int s = 0, ph = 0;
        for (int kb = 3; kb < 16; kb++) {
          mbar_wait(bar_empty + 8 * s, ph);
          small_load(maps, sbase, bar_full, (c - 64) * 2 + rank, s, kb);
          if (++s == 3) { s = 0; ph ^= 1; }
        }
      }
    }
    if (MODE == 0 && tid == 288 && c >= 32) {
      const uint32_t tag = *reinterpret_cast<volatile uint32_t*>(&g_epoch) + 1;
      mbar_wait(bar_empty + 8 * G_STAGES, 0);
      asm volatile("st.release.gpu.global.u32 [%0], %1;" ::"l"(g_k1flag + blockIdx.x), "r"(tag) : "memory");
    }
    __syncwarp();
    cluster_sync();
  } else {
    asm volatile("setmaxnreg.inc.sync.aligned.u32 232;");
    GCtx x;
    x.sbase = sbase; x.bar_full = bar_full; x.bar_empty = bar_empty; x.stg = sbase + G_STG_OFF + warp * 4096;
    x.tmode = MODE; x.wg = warp >> 2; x.wrow = warp * 16; x.lane = lane;
    if (!small) {
      float acc[128];
      x.mma(acc, 0);
      if (MODE == 0) {
#pragma unroll 1
        for (int kb = 1; kb < 16; kb++) x.step(acc, kb);
        wg_wait<0>();
        x.release(15);
        fence_regs(acc);
        GT(3); GTW(6);
        const Tile t = get_tile<0>(maps, c, rank, 0);
        const int orow = t.row0 + x.wrow;
        uint32_t p[64];
#pragma unroll
        for (int i = 0; i < 64; i++) p[i] = pack_bf16(acc[2 * i], acc[2 * i + 1]);
#pragma unroll
        for (int i = 0; i < 64; i++) asm volatile("" : "+r"(p[i])::"memory");
        GT(4);
        x.mma(acc, 0);
        x.mma(acc, 1);
        store_packed<0>(p, x.stg, maps, t.out_col, orow, lane);
        write_norms4_packed<0>(p, t.out_col >> 5, orow >> 4, lane);
        wg_wait<1>(); x.release(0);
        x.mma(acc, 2);
        write_norms4_packed<1>(p, (t.out_col >> 5) + 4, orow >> 4, lane);
        wg_wait<1>(); x.release(1);
        x.mma(acc, 3);
        x.stg_free();
        store_packed<1>(p, x.stg, maps, t.out_col + 128, orow, lane);
        wg_wait<1>(); x.release(2);
        GT(5);
#pragma unroll 1
        for (int kb = 4; kb < SKEW0; kb++) {
          x.step(acc, kb);
          if (kb == QDONE_KB && c >= 32) {
            if (lane == 0) bulk_wait<0>();
            __syncwarp();
            if (lane == 0) mbar_arrive(bar_empty + 8 * G_STAGES);
          }
        }
        skewed_tail(acc, x);
        GT(7); GTW(9);
        last_epilogue<0>(acc, get_tile<0>(maps, c, rank, 1), x, maps);
        GT(8);
      } else {
#pragma unroll 1
        for (int kb = 1; kb < SKEW0; kb++) x.step(acc, kb);
        skewed_tail(acc, x);
        GT(4); GTW(6);
        last_epilogue<1>(acc, get_tile<1>(maps, c, rank, 0), x, maps);
        GT(5); GTW(9);
      }
    } else {
      const int idx = (c - 64) * 2 + rank;
      float acc[4][32];
      int s = 0, ph = 0;
#pragma unroll 1
      for (int kb = 0; kb < 16; kb++) {
        mbar_wait(bar_full + 8 * s, ph);
        const uint32_t st = sbase + s * S_STAGE_BYTES;
        const uint64_t dB = make_desc(st + 65536, 4096, 512, 2);
        wg_fence();
#pragma unroll
        for (int it = 0; it < 4; it++) {
          const uint64_t dA = make_desc(st + it * 16384 + x.wg * 8192, 16, 1024, 1);
#pragma unroll
          for (int k = 0; k < 4; k++) wgmma_n64_ss_tb(acc[it], dA + 2 * k, dB + 64 * k, kb | k);
        }
        wg_commit();
        wg_wait<0>();
        if (lane == 0) mbar_arrive(bar_empty + 8 * s);
        if (++s == 3) { s = 0; ph ^= 1; }
      }
      bar_sync(7, 256);
#pragma unroll
      for (int it = 0; it < 4; it++) {
        fence_regs(acc[it]);
        const int orow = (idx * 4 + it) * 128 + x.wrow;
        const uint32_t hmask = write_norms2(acc[it], 128, orow >> 4, lane);
        store_tile<0, 1, true, true>(acc[it], x.wrow >= HC ? VSCALE : 1.0f, hmask, sbase + warp * 8192 + it * 2048, maps, 4096, orow, lane);
      }
    }
    if (MODE == 0 && small) {
      if (lane == 0) bulk_wait<0>();
      __syncwarp();
      if (lane == 0) mbar_arrive(bar_empty + 8 * G_STAGES);
    }
    if (lane == 0) bulk_wait_read<0>();
    GT(10);
    cluster_sync();
    GT(11); GTG(15);
  }
}
struct AttnMaps { CUtensorMap q, kva, kvb; unsigned short rec[133 * 8]; };

constexpr float QS_ATT = QSCALE;
constexpr int A_STAGES = 8;
constexpr int A_STAGE_BYTES = 16384;
constexpr int A_Q_OFF = A_STAGES * A_STAGE_BYTES;
constexpr int A_O_OFF = A_Q_OFF + 16384;
constexpr int A_ONES_OFF = A_O_OFF + 16384;
constexpr int A_BAR_OFF = A_ONES_OFF + 2048;
constexpr int A_PART_OFF = A_BAR_OFF + 256;
constexpr int A_PART_BYTES = 7 * 128 * 16;
constexpr int A_NRM_OFF = A_PART_OFF + 4 * A_PART_BYTES;
constexpr int A_NRM_BYTES = 1088;
constexpr int A_SMEM = A_NRM_OFF + A_NRM_BYTES + 1024;
constexpr int A_THREADS = 512;
constexpr int A_PF = 3;
constexpr int A_GRID = 132;
constexpr int A_EARLY = 4;
const short h_first_step[A_GRID + 1] = {
  0, 68, 136, 204, 272, 336, 400, 464, 528, 592, 656, 720, 784, 848, 912, 976, 1040, 1104, 1168,
  1232, 1296, 1360, 1424, 1487, 1549, 1611, 1673, 1735, 1797, 1859, 1921, 1984, 2047, 2109, 2171, 2233, 2295, 2357,
  2419, 2481, 2544, 2607, 2669, 2731, 2793, 2855, 2917, 2979, 3041, 3104, 3167, 3229, 3291, 3353, 3415, 3477, 3538,
  3600, 3663, 3725, 3787, 3848, 3909, 3970, 4032, 4094, 4155, 4216, 4277, 4338, 4400, 4462, 4523, 4584, 4645, 4706,
  4768, 4830, 4891, 4952, 5013, 5074, 5136, 5198, 5259, 5320, 5381, 5442, 5504, 5566, 5627, 5688, 5749, 5810, 5872,
  5934, 5995, 6056, 6117, 6178, 6240, 6302, 6363, 6424, 6485, 6546, 6608, 6670, 6731, 6792, 6853, 6914, 6976, 7038,
  7099, 7160, 7221, 7282, 7343, 7404, 7465, 7526, 7587, 7648, 7710, 7770, 7830, 7890, 7951, 8011, 8071, 8131, 8192};

__device__ __forceinline__ uint32_t ex2_pair_f16(uint32_t x) {
  uint32_t t, w, u, p;
  asm("add.rn.f16x2 %0, %1, %2;" : "=r"(t) : "r"(x), "r"(0x64436443u));
  asm("fma.rn.f16x2 %0, %1, %2, %3;" : "=r"(w) : "r"(t), "r"(0xa27ba27bu), "r"(0x4aea4aeau));
  asm("fma.rn.f16x2 %0, %1, %2, %3;" : "=r"(u) : "r"(x), "r"(0x227b227bu), "r"(w));
  asm("fma.rn.f16x2 %0, %1, %1, %2;" : "=r"(p) : "r"(u), "r"(0x1da31dd5u));
  uint32_t r;
  asm("{\n.reg .u32 s;\nshf.l.wrap.b32 s, 0, %1, 7;\nadd.u32 %0, s, %2;\n}\n" : "=r"(r) : "r"(t), "r"(p));
  return r;
}

#define QK_EARLY 0
#define PV_GROUPS 2
constexpr uint32_t DESC_HI = (512u >> 4) | (2u << 30);
constexpr uint32_t V_K_STEP = (1024u >> 4) - ((1024u >> 4) << 16);
constexpr uint32_t V_STAGE_STEP = (16384u >> 4) - ((16384u >> 4) << 16);
__host__ __device__ constexpr uint32_t v_slab(int k) { return k * V_K_STEP + (16 * k >= HC ? (1024u >> 4) << 16 : 0u); }
__device__ __forceinline__ uint64_t desc64(uint32_t lo, uint32_t hi) { return ((uint64_t)hi << 32) | lo; }

__device__ __forceinline__ bool elect_one() {
  uint32_t pred;
  asm volatile("{\n.reg .pred p;\nelect.sync _|p, 0xffffffff;\nselp.u32 %0, 1, 0, p;\n}\n" : "=r"(pred));
  return pred != 0;
}
__device__ __forceinline__ void tma_load_3d(uint32_t dst, const CUtensorMap* map, uint32_t bar, int c0, int c1, int c2) {
  asm volatile("cp.async.bulk.tensor.3d.shared::cluster.global.mbarrier::complete_tx::bytes [%0], [%1, {%3, %4, %5}], [%2];"
               ::"r"(dst), "l"(map), "r"(bar), "r"(c0), "r"(c1), "r"(c2) : "memory");
}
__device__ __forceinline__ void issue_kv(const AttnMaps& maps, uint32_t sbase, int g, int top, uint32_t u) {
  const int s = g & (A_STAGES - 1);
  const uint32_t bar_full = sbase + A_BAR_OFF + 8 * s, bar_empty = bar_full + 8 * A_STAGES;
  const bool b = u >> 8;
  if (g >= A_STAGES) mbar_wait(bar_empty, ((g >> 3) - 1) & 1);
  if (elect_one()) {
    mbar_expect_tx(bar_full, A_STAGE_BYTES);
    tma_load_3d(sbase + s * A_STAGE_BYTES, b ? &maps.kvb : &maps.kva, bar_full, b ? 0 : ((u >> 3) & 31) * 32, ((top - g) & 15) * 128, 0);
  }
}
__device__ __forceinline__ void bulk_load(uint32_t dst, const void* src, uint32_t bytes, uint32_t bar) {
  asm volatile("cp.async.bulk.shared::cluster.global.mbarrier::complete_tx::bytes [%0], [%1], %2, [%3];"
               ::"r"(dst), "l"(src), "r"(bytes), "r"(bar) : "memory");
}
__device__ __forceinline__ void issue_q(const AttnMaps& maps, uint32_t sbase, uint32_t u, int part) {
  const uint32_t bar_qfull = sbase + A_BAR_OFF + 16 * A_STAGES;
  const int b = u >> 8, h = (u >> 3) & 31, qt = u & 7;
  if (elect_one()) {
    if (part == 0) {
      mbar_expect_tx(bar_qfull, 16384);
      tma_load_2d(sbase + A_Q_OFF, &maps.q, bar_qfull, b * 3072 + h * 32, qt * 256);
    } else {
      const int first = part == 3 ? (b * 96 + h) * 128 + qt * 16 : b ? (127 + part) * 128 : (32 * part + h) * 128;
      const uint32_t bytes = part == 3 ? 64 : 512;
      mbar_expect_tx(bar_qfull, bytes);
      bulk_load(sbase + A_NRM_OFF - 512 + 512 * part, g_nrm + first, bytes, bar_qfull);
    }
  }
}

struct Piece {
  int it;
  int u, g0, g1;
  uint32_t uu;
  int top, n;
};
#define B2A ((pc.uu & 0x01000100u) == 0x100u)
#define PREFETCH() do { if (issuer) { \
      if ((g & 3) == wg && g + A_PF < pc.n) { \
        const bool nx = g + A_PF >= pc.g1; \
        if (nx && B2A) pdl_wait(); \
        issue_kv(maps, sbase, g + A_PF, pc.top, nx ? pc.uu >> 16 : pc.uu & 0xffff); \
      } \
      if (g == gq && pc.g1 < pc.n) { \
        mbar_wait(bar_qempty, pc.it & 1); \
        if (B2A) pdl_wait(); \
        issue_q(maps, sbase, pc.uu >> 16, wg); \
      } \
    } } while (0)

#define AT(k) do {} while (0)
#define TR(k) do {} while (0)

__device__ __forceinline__ int fresh_lane() {
  int l;
  asm volatile("mov.u32 %0, %%laneid;" : "=r"(l));
  return l;
}
__device__ __forceinline__ bool load_q(uint32_t (&qf)[8], uint32_t (&qh)[8], uint32_t sbase, int it, int warp, uint32_t u) {
  const int lane = fresh_lane();
  const uint32_t bar_qfull = sbase + A_BAR_OFF + 16 * A_STAGES, bar_qempty = bar_qfull + 8;
  mbar_wait(bar_qfull, it & 1);
  uint32_t kn[4], vn[4], qn;
  asm volatile("ld.shared.v4.b32 {%0, %1, %2, %3}, [%4];" : "=r"(kn[0]), "=r"(kn[1]), "=r"(kn[2]), "=r"(kn[3]) : "r"(sbase + A_NRM_OFF + lane * 16) : "memory");
  asm volatile("ld.shared.v4.b32 {%0, %1, %2, %3}, [%4];" : "=r"(vn[0]), "=r"(vn[1]), "=r"(vn[2]), "=r"(vn[3]) : "r"(sbase + A_NRM_OFF + 512 + lane * 16) : "memory");
  asm volatile("ld.shared.b32 %0, [%1];" : "=r"(qn) : "r"(sbase + A_NRM_OFF + 1024 + (lane & 15) * 4) : "memory");
  const int mi = lane >> 3;
  const int row = warp * 16 + (lane & 7) + (mi & 1) * 8;
  const uint32_t rbase = sbase + A_Q_OFF + row * 64;
  const int sw = (row >> 1) & 3;
  ldmatrix_x4(rbase + (((mi >> 1) ^ sw) << 4), qf[0], qf[1], qf[2], qf[3]);
  ldmatrix_x4(rbase + (((2 + (mi >> 1)) ^ sw) << 4), qf[4], qf[5], qf[6], qf[7]);
  const float k2 = __uint_as_float(__reduce_max_sync(0xffffffffu, max(max(kn[0], kn[1]), max(kn[2], kn[3]))));
  const float v2 = __uint_as_float(__reduce_max_sync(0xffffffffu, max(max(vn[0], vn[1]), max(vn[2], vn[3]))));
  const float q2 = __uint_as_float(__reduce_max_sync(0xffffffffu, qn)) * (QS_ATT * QS_ATT);
  bool ok = (k2 >= 0.0f) && !(__float_as_uint(k2) >> 31) && (q2 * k2 <= 3600.0f) && (q2 <= 1048576.0f) && (v2 <= 1.2e24f) && (v2 >= 8.3e-25f);
#pragma unroll
  for (int i = 0; i < 8; i++)
    qh[i] = pack_f16(__uint_as_float(qf[i] << 16) * QS_ATT, __uint_as_float(qf[i] & 0xffff0000u) * QS_ATT);
  __syncwarp();
  if (lane == 0) mbar_arrive(bar_qempty);
  return __ballot_sync(0xffffffffu, ok) != 0;
}

__device__ __forceinline__ uint4* part_global(int cta, int wg) { return g_part + (size_t)(cta * 4 + wg) * (A_PART_BYTES / 16); }
template <bool SLOW>
__device__ __forceinline__ void part_out(const float (&o)[20], float m0, float m1, uint32_t sbase, int warp) {
  const int wg = warp >> 2, wwarp = warp & 3, lane = fresh_lane();
  const uint32_t buf = sbase + A_PART_OFF + wg * A_PART_BYTES, addr = buf + (wwarp * 32 + lane) * 16;
  uint32_t tag;
  asm volatile("ld.shared.u32 %0, [%1];" : "=r"(tag) : "r"(sbase + A_BAR_OFF + 184) : "memory");
#pragma unroll
  for (int i = 0; i < (SLOW ? 7 : 6); i++) {
    const float a = i < 6 ? o[i < 6 ? 3 * i : 0] : m0, b = i < 5 ? o[i < 5 ? 3 * i + 1 : 0] : i == 5 ? o[16] : m1;
    const float c = i < 5 ? o[i < 5 ? 3 * i + 2 : 0] : i == 5 ? o[18] : 0.f;
    asm volatile("st.shared.v4.b32 [%0], {%1, %2, %3, %4};" ::"r"(addr + i * 2048), "r"(__float_as_uint(a)), "r"(__float_as_uint(b)),
                 "r"(__float_as_uint(c)), "r"(tag) : "memory");
  }
  fence_proxy_async();
  bar_sync(1 + wg, 128);
  if (wwarp == 0 && lane == 0) {
    asm volatile("cp.async.bulk.global.shared::cta.bulk_group [%0], [%1], %2;"
                 ::"l"(part_global(blockIdx.x, wg)), "r"(buf), "r"((SLOW ? 7 : 6) * 2048) : "memory");
    bulk_commit();
  }
}
template <bool SLOW>
__device__ __forceinline__ void part_in(float (&o)[20], float& m0, float& m1, uint32_t sbase, int warp) {
  const int wg = warp >> 2, wwarp = warp & 3, lane = fresh_lane();
  constexpr int N = SLOW ? 7 : 6;
  const uint32_t addr = sbase + A_PART_OFF + wg * A_PART_BYTES + (wwarp * 32 + lane) * 16;
  uint32_t tag, w[N][4];
  asm volatile("ld.shared.u32 %0, [%1];" : "=r"(tag) : "r"(sbase + A_BAR_OFF + 184) : "memory");
  mbar_wait(sbase + A_BAR_OFF + 144 + 8 * wg, 0);
  bool ok = true;
#pragma unroll
  for (int i = 0; i < N; i++) {
    asm volatile("ld.shared.v4.b32 {%0, %1, %2, %3}, [%4];" : "=r"(w[i][0]), "=r"(w[i][1]), "=r"(w[i][2]), "=r"(w[i][3]) : "r"(addr + i * 2048) : "memory");
    ok = ok && w[i][3] == tag;
  }
  if (!ok) {
    const uint4* g = part_global(blockIdx.x - 1, wg) + wwarp * 32 + lane;
    uint32_t n = 0;
#pragma unroll 1
    do {
      ok = true;
#pragma unroll
      for (int i = 0; i < N; i++) {
        asm volatile("ld.volatile.global.v4.b32 {%0, %1, %2, %3}, [%4];" : "=r"(w[i][0]), "=r"(w[i][1]), "=r"(w[i][2]), "=r"(w[i][3]) : "l"(g + i * 128) : "memory");
        ok = ok && w[i][3] == tag;
      }
    } while (!ok && ++n < (1u << 20));
  }
#pragma unroll
  for (int i = 0; i < 5; i++)
#pragma unroll
    for (int k = 0; k < 3; k++) o[3 * i + k] = __uint_as_float(w[i][k]);
  o[15] = __uint_as_float(w[5][0]); o[16] = __uint_as_float(w[5][1]); o[17] = 0.f; o[18] = __uint_as_float(w[5][2]); o[19] = 0.f;
  if (SLOW) { m0 = __uint_as_float(w[N - 1][0]); m1 = __uint_as_float(w[N - 1][1]); }
}

__device__ __forceinline__ void store_o(const AttnMaps& maps, const float (&o)[20], uint32_t sbase, const Piece& pc, int warp) {
  const int lane = fresh_lane();
  const float l0 = __shfl_sync(0xffffffffu, o[16], lane & ~3), l1 = __shfl_sync(0xffffffffu, o[18], lane & ~3);
  const float i0 = rcp(l0), i1 = rcp(l1);
  const uint32_t stg = sbase + A_O_OFF + warp * 1024;
  {
    const int mi = lane >> 3;
    const int row = (lane & 7) + (mi & 1) * 8;
    const int sw = (row >> 1) & 3;
#pragma unroll
    for (int jj = 0; jj < 2; jj++) {
      const int j = 2 * jj;
      stmatrix_x4(stg + row * 64 + (((2 * jj + (mi >> 1)) ^ sw) << 4),
                  pack_bf16(o[4 * j] * i0, o[4 * j + 1] * i0), pack_bf16(o[4 * j + 2] * i1, o[4 * j + 3] * i1),
                  pack_bf16(o[4 * j + 4] * i0, o[4 * j + 5] * i0), pack_bf16(o[4 * j + 6] * i1, o[4 * j + 7] * i1));
    }
  }
  __syncwarp();
  const int u = pc.uu & 0xffff, r = lane >> 2, c = lane & 3;
  __nv_bfloat16* dst = g_o + (size_t)((u & 7) * 256 + warp * 16 + r) * O_LD + (u >> 8) * 1024 + ((u >> 3) & 31) * 32 + c * 8;
#pragma unroll
  for (int h = 0; h < 2; h++) {
    uint32_t w[4];
    asm volatile("ld.shared.v4.b32 {%0, %1, %2, %3}, [%4];" : "=r"(w[0]), "=r"(w[1]), "=r"(w[2]), "=r"(w[3])
                 : "r"(stg + (r + 8 * h) * 64 + ((c ^ ((r >> 1) & 3)) << 4)) : "memory");
    asm volatile("st.global.v4.b32 [%0], {%1, %2, %3, %4};" ::"l"(dst + h * 8 * O_LD), "r"(w[0]), "r"(w[1]), "r"(w[2]), "r"(w[3]) : "memory");
  }
  __syncwarp();
  const int first = pc.top + 1 - pc.n;
  if (pc.u - 2 == (first >> 4) && (first & 15) != 0 && (warp & 3) == 0 && lane == 0) {
    const int wg = warp >> 2;
    const uint32_t bar = sbase + A_BAR_OFF + 144 + 8 * wg;
    bulk_wait_read<0>();
    mbar_expect_tx(bar, A_PART_BYTES);
    asm volatile("cp.async.bulk.shared::cluster.global.mbarrier::complete_tx::bytes [%0], [%1], %2, [%3];"
                 ::"r"(sbase + A_PART_OFF + wg * A_PART_BYTES), "l"(part_global(blockIdx.x - 1, wg)), "r"(A_PART_BYTES), "r"(bar) : "memory");
  }
}

struct Scores {
  float sf[HC > 0 ? HC / 2 : 2];
  uint32_t sh[(128 - HC) / 4];
};
__device__ __forceinline__ void issue_qk(Scores& S, const uint32_t (&qf)[8], uint32_t k_lo) {
  wg_fence();
  wgmma_f16in_f32(S.sf, qf[0], qf[1], qf[2], qf[3], desc64(k_lo, DESC_HI), 0);
  wgmma_f16in_f16(S.sh, qf[0], qf[1], qf[2], qf[3], desc64(k_lo + HC * 4, DESC_HI), 0);
  wgmma_f16in_f32(S.sf, qf[4], qf[5], qf[6], qf[7], desc64(k_lo + 2, DESC_HI), 1);
  wgmma_f16in_f16(S.sh, qf[4], qf[5], qf[6], qf[7], desc64(k_lo + HC * 4 + 2, DESC_HI), 1);
  wg_commit();
}

__device__ __forceinline__ void softmax_pv(const Scores& S, float (&o)[20], uint32_t v_lo) {
#pragma unroll
  for (int c = 0; c < PV_GROUPS; c++) {
    constexpr int KPG = 8 / PV_GROUPS, NM = HC / 16;
    uint32_t p[4 * KPG];
    int slab[KPG];
#pragma unroll
    for (int kk = 0; kk < KPG; kk++) {
      int nm_before = 0, nm_here = 0;
      for (int m = 0; m < NM; m++) { if (m % PV_GROUPS < c) nm_before++; if (m % PV_GROUPS == c) nm_here++; }
      slab[kk] = kk < nm_here ? c + kk * PV_GROUPS : NM + (c * KPG - nm_before) + (kk - nm_here);
#pragma unroll
      for (int i = 0; i < 4; i++)
        p[4 * kk + i] = slab[kk] < NM ? pack_bf16(ex2(S.sf[(slab[kk] < NM ? slab[kk] : 0) * 8 + 2 * i]), ex2(S.sf[(slab[kk] < NM ? slab[kk] : 0) * 8 + 2 * i + 1]))
                                      : ex2_pair_f16(S.sh[(slab[kk] < NM ? 0 : slab[kk] - NM) * 4 + i]);
    }
#pragma unroll
    for (int i = 0; i < 4 * KPG; i++) asm volatile("" : "+r"(p[i]));
    wg_fence();
#pragma unroll
    for (int kk = 0; kk < KPG; kk++)
      wgmma_n40_rs_tb(o, p[4 * kk], p[4 * kk + 1], p[4 * kk + 2], p[4 * kk + 3], desc64(v_lo + v_slab(slab[kk]), DESC_HI), 1);
  }
  wg_commit();
}
__device__ __forceinline__ void fence_scores(Scores& S) {
  fence_regs(S.sf);
#pragma unroll
  for (int i = 0; i < (128 - HC) / 4; i++) asm volatile("" : "+r"(S.sh[i])::"memory");
}

__device__ __forceinline__ void attn_unit_fast(const AttnMaps& maps, const uint32_t sbase, const Piece& pc, const int warp, const int lane,
                                               uint32_t (&qf)[8]) {
  const uint32_t bar_full = sbase + A_BAR_OFF, bar_empty = bar_full + 8 * A_STAGES;
  const uint32_t bar_qempty = bar_empty + 8 * A_STAGES + 8;
  const int wg = warp >> 2, wwarp = warp & 3;
  const bool issuer = (wwarp == wg);
  const uint32_t k_lo0 = (sbase >> 4) | (1u << 16);
  const uint32_t v_lo0 = ((sbase + 8192) >> 4) | (((A_ONES_OFF - 8192) >> 4) << 16);
  const int gq = min(pc.g0 + 8, pc.g1 - 1);
  float o[20];
  if (pc.g1 == pc.n && ((pc.top + 1 - pc.n) & 15) != 0) {
    float m0, m1;
    part_in<false>(o, m0, m1, sbase, warp);
  } else {
#pragma unroll
    for (int i = 0; i < 20; i++) o[i] = 0.f;
  }
  if (pc.it == 0) AT(3);
  fence_regs(o);
  __syncwarp();
  Scores S;
#pragma unroll 1
  for (int g = pc.g0; g < pc.g1; g++) {
    const int s = g & 7;
    TR(0);
    mbar_wait(bar_full + 8 * s, (g >> 3) & 1);
    TR(1);
    if (g == 0) AT(4);
    issue_qk(S, qf, k_lo0 + s * (A_STAGE_BYTES >> 4));
    PREFETCH();
    wg_wait<0>();
    fence_scores(S);
    TR(2);
    softmax_pv(S, o, v_lo0 + s * V_STAGE_STEP);
    TR(5);
    wg_wait<0>();
    fence_regs(o);
    if (lane == 0) mbar_arrive(bar_empty + 8 * s);
    TR(6);
  }
  AT(pc.it < 4 ? 5 + pc.it : 15);
  if (pc.it == 0 && (pc.top & 15) != 15) part_out<false>(o, 0.f, 0.f, sbase, warp);
  else store_o(maps, o, sbase, pc, warp);
}

__device__ __forceinline__ void attn_unit_slow(const AttnMaps& maps, const uint32_t sbase, const Piece& pc, const int warp, const int lane,
                                               const uint32_t (&qf)[8]) {
  const uint32_t bar_full = sbase + A_BAR_OFF, bar_empty = bar_full + 8 * A_STAGES;
  const uint32_t bar_qempty = bar_empty + 8 * A_STAGES + 8;
  const int wg = warp >> 2, wwarp = warp & 3;
  const bool issuer = (wwarp == wg);
  const uint32_t k_lo0 = (sbase >> 4) | (1u << 16);
  const uint32_t v_lo0 = ((sbase + 8192) >> 4) | (((A_ONES_OFF - 8192) >> 4) << 16);
  const int gq = min(pc.g0 + 8, pc.g1 - 1);
  float o[20];
#pragma unroll
  for (int i = 0; i < 20; i++) o[i] = 0.f;
  float m0 = -INFINITY, m1 = -INFINITY;
  if (pc.g1 == pc.n && ((pc.top + 1 - pc.n) & 15) != 0) part_in<true>(o, m0, m1, sbase, warp);
#pragma unroll 1
  for (int g = pc.g0; g < pc.g1; g++) {
    const int s = g & 7, j = (pc.top - g) & 15;
    mbar_wait(bar_full + 8 * s, (g >> 3) & 1);
    const uint32_t k_lo = k_lo0 + s * (A_STAGE_BYTES >> 4), v_lo = v_lo0 + s * V_STAGE_STEP;
    PREFETCH();
    {
      const int tid = warp * 32 + lane;
      const int u = pc.uu & 0xffff;
      const int kg = (u >> 8) ? 128 : 32 + ((u >> 3) & 31);
      if (!(__float_as_uint(__ldcg(g_nrm + kg * 128 + j * 8 + (tid >> 6))) >> 31)) {
        const uint32_t addr = sbase + s * A_STAGE_BYTES + tid * 16;
        uint32_t w[4];
        asm volatile("ld.shared.v4.b32 {%0, %1, %2, %3}, [%4];" : "=r"(w[0]), "=r"(w[1]), "=r"(w[2]), "=r"(w[3]) : "r"(addr) : "memory");
#pragma unroll
        for (int i = 0; i < 4; i++) {
          const float2 f = __half22float2(*reinterpret_cast<const __half2*>(&w[i]));
          w[i] = pack_bf16(f.x, f.y);
        }
        asm volatile("st.shared.v4.b32 [%0], {%1, %2, %3, %4};" ::"r"(addr), "r"(w[0]), "r"(w[1]), "r"(w[2]), "r"(w[3]) : "memory");
      }
      fence_proxy_async();
      bar_sync(5, A_THREADS);
    }
#pragma unroll 1
    for (int hf = 0; hf < 2; hf++) {
      float sc[32];
      wg_fence();
      wgmma_n64_rs(sc, qf[0], qf[1], qf[2], qf[3], desc64(k_lo + hf * 256, DESC_HI), 0);
      wgmma_n64_rs(sc, qf[4], qf[5], qf[6], qf[7], desc64(k_lo + hf * 256 + 2, DESC_HI), 1);
      wg_commit();
      wg_wait<0>();
      fence_regs(sc);
#pragma unroll
      for (int i = 0; i < 32; i++) sc[i] *= QS_ATT;
      float n0 = m0, n1 = m1;
#pragma unroll
      for (int i = 0; i < 8; i++) {
        n0 = fmaxf(n0, fmaxf(sc[4 * i], sc[4 * i + 1]));
        n1 = fmaxf(n1, fmaxf(sc[4 * i + 2], sc[4 * i + 3]));
      }
      n0 = fmaxf(n0, __shfl_xor_sync(0xffffffffu, n0, 1)); n0 = fmaxf(n0, __shfl_xor_sync(0xffffffffu, n0, 2));
      n1 = fmaxf(n1, __shfl_xor_sync(0xffffffffu, n1, 1)); n1 = fmaxf(n1, __shfl_xor_sync(0xffffffffu, n1, 2));
      const float z0 = (n0 == -INFINITY) ? 0.f : n0, z1 = (n1 == -INFINITY) ? 0.f : n1;
      const float a0 = ex2(m0 - z0), a1 = ex2(m1 - z1);
      m0 = n0; m1 = n1;
#pragma unroll
      for (int i = 0; i < 5; i++) { o[4 * i] *= a0; o[4 * i + 1] *= a0; o[4 * i + 2] *= a1; o[4 * i + 3] *= a1; }
      uint32_t p[16];
#pragma unroll
      for (int i = 0; i < 8; i++) {
        const float f = (HC > 0 && hf * 64 + i * 8 >= HC) ? 1.0f / VSCALE : 1.0f;
        p[2 * i] = pack_bf16(ex2(sc[4 * i] - z0) * f, ex2(sc[4 * i + 1] - z0) * f);
        p[2 * i + 1] = pack_bf16(ex2(sc[4 * i + 2] - z1) * f, ex2(sc[4 * i + 3] - z1) * f);
      }
      wg_fence();
#pragma unroll
      for (int kk = 0; kk < 4; kk++)
        wgmma_n40_rs_tb(o, p[4 * kk], p[4 * kk + 1], p[4 * kk + 2], p[4 * kk + 3],
                        desc64(v_lo + (hf ? v_slab(4 + kk) : v_slab(kk)), DESC_HI), 1);
      wg_commit();
      wg_wait<0>();
      fence_regs(o);
    }
    if (lane == 0) mbar_arrive(bar_empty + 8 * s);
  }
  if (pc.it == 0 && (pc.top & 15) != 15) part_out<true>(o, m0, m1, sbase, warp);
  else store_o(maps, o, sbase, pc, warp);
}

__global__ void __launch_bounds__(A_THREADS, 1) attn_kernel(const __grid_constant__ AttnMaps maps) {
  extern __shared__ uint8_t smem_raw[];
  const uint32_t sbase = __shfl_sync(0xffffffffu, (smem_u32(smem_raw) + 1023u) & ~1023u, 0);
  uint8_t* sgen = smem_raw + (sbase - smem_u32(smem_raw));
  const int tid = threadIdx.x, lane = tid & 31;
  const int warp = __shfl_sync(0xffffffffu, tid >> 5, 0);
  AT(0);
  pdl_launch();
  const unsigned short* rec = maps.rec + blockIdx.x * 8;
  Piece pc;
  pc.top = rec[0];
  pc.n = rec[1];
  uint32_t tag = 0;
  if (warp == 0) {
    uint32_t f[4];
    const uint32_t* fl = g_k1flag + 64 + 4 * min(lane, 16);
    asm volatile("ld.relaxed.gpu.global.u32 %0, [%1];" : "=r"(tag) : "l"(&g_epoch) : "memory");
    uint32_t n = 0;
#pragma unroll 1
    while (true) {
      asm volatile("ld.acquire.gpu.global.v4.u32 {%0, %1, %2, %3}, [%4];" : "=r"(f[0]), "=r"(f[1]), "=r"(f[2]), "=r"(f[3]) : "l"(fl) : "memory");
      if (__all_sync(0xffffffffu, f[0] == tag + 1 && f[1] == tag + 1 && f[2] == tag + 1 && f[3] == tag + 1)) break;
      if (++n > (1u << 16)) { pdl_wait(); break; }
      __nanosleep(100);
    }
    asm volatile("fence.proxy.async.global;" ::: "memory");
    if (lane == 0) *reinterpret_cast<uint32_t*>(sgen + A_BAR_OFF + 184) = tag + 1;
    AT(2);
  }
  if (tid == 32) {
    const uint32_t bar = sbase + A_BAR_OFF;
    for (int s = 0; s < A_STAGES; s++) { mbar_init(bar + 8 * s, 1); mbar_init(bar + 8 * (A_STAGES + s), 16); }
    mbar_init(bar + 16 * A_STAGES, 4); mbar_init(bar + 16 * A_STAGES + 8, 16);
    for (int s = 0; s < 4; s++) mbar_init(bar + 144 + 8 * s, 1);
    fence_mbar_init();
  }
  if (tid >= 64 && tid < 192) {
    *reinterpret_cast<uint4*>(sgen + A_ONES_OFF + (tid - 64) * 16) = make_uint4((tid < 128 || HC == 0) ? 0x00003F80u : 0x00003F35u, 0, 0, 0);
    fence_proxy_async();
  }
  if (tid == 192) { prefetch_tmap(&maps.q); prefetch_tmap(&maps.kva); prefetch_tmap(&maps.kvb); }
  __syncthreads();
  AT(1);
  if (warp == 0) {
    const uint32_t u0 = rec[2], u1 = rec[3];
    if (!(u0 & 0x100) || ((pc.top & 15) < A_PF - 1 && !(u1 & 0x100))) pdl_wait();
    issue_q(maps, sbase, u0, 0);
    issue_kv(maps, sbase, 0, pc.top, u0);
    for (int part = 1; part < 4; part++) issue_q(maps, sbase, u0, part);
    for (int g = 1; g < A_PF; g++) issue_kv(maps, sbase, g, pc.top, g <= (pc.top & 15) ? u0 : u1);
  }
  pc.g0 = 0;
  pc.u = pc.top >> 4;
#pragma unroll 1
  for (pc.it = 0; pc.g0 < pc.n; pc.it++, pc.u--) {
    pc.g1 = min(pc.top + 1 - 16 * pc.u, pc.n);
    pc.uu = rec[2 + pc.it] | ((uint32_t)rec[3 + pc.it] << 16);
    uint32_t qf[8], qh[8];
    if (load_q(qf, qh, sbase, pc.it, warp, pc.uu & 0xffff)) attn_unit_fast(maps, sbase, pc, warp, lane, qh);
    else attn_unit_slow(maps, sbase, pc, warp, lane, qf);
    pc.g0 = pc.g1;
  }
  pdl_wait();
  AT(9);
  if ((tid & 127) == 0) bulk_wait<0>();
  AT(10);
}
typedef CUresult (*EncodeFn)(CUtensorMap*, CUtensorMapDataType, cuuint32_t, void*, const cuuint64_t*, const cuuint64_t*,
                             const cuuint32_t*, const cuuint32_t*, CUtensorMapInterleave, CUtensorMapSwizzle,
                             CUtensorMapL2promotion, CUtensorMapFloatOOBfill);

void make_map(EncodeFn enc, CUtensorMap* m, const void* ptr, uint64_t cols, uint64_t rows, uint64_t ld, uint32_t box_c,
              uint32_t box_r, CUtensorMapSwizzle swz) {
  cuuint64_t dims[2] = {cols, rows};
  cuuint64_t strides[1] = {ld * 2};
  cuuint32_t box[2] = {box_c, box_r};
  cuuint32_t es[2] = {1, 1};
  enc(m, CU_TENSOR_MAP_DATA_TYPE_BFLOAT16, 2, const_cast<void*>(ptr), dims, strides, box, es, CU_TENSOR_MAP_INTERLEAVE_NONE,
      swz, CU_TENSOR_MAP_L2_PROMOTION_L2_256B, CU_TENSOR_MAP_FLOAT_OOB_FILL_NONE);
}

void make_map_kv(EncodeFn enc, CUtensorMap* m, const void* ptr, uint64_t cols, uint64_t kv_stride) {
  cuuint64_t dims[3] = {cols, 2048, 2};
  cuuint64_t strides[2] = {(cuuint64_t)QKV_LD * 2, kv_stride * 2};
  cuuint32_t box[3] = {32, 128, 2};
  cuuint32_t es[3] = {1, 1, 1};
  enc(m, CU_TENSOR_MAP_DATA_TYPE_BFLOAT16, 3, const_cast<void*>(ptr), dims, strides, box, es, CU_TENSOR_MAP_INTERLEAVE_NONE,
      CU_TENSOR_MAP_SWIZZLE_64B, CU_TENSOR_MAP_L2_PROMOTION_L2_256B, CU_TENSOR_MAP_FLOAT_OOB_FILL_NONE);
}

void make_map_w(EncodeFn enc, CUtensorMap* m, const void* ptr, uint64_t cols) {
  cuuint64_t dims[3] = {64, 1024, cols / 64};
  cuuint64_t strides[2] = {cols * 2, 128};
  cuuint32_t box[3] = {64, 64, 2};
  cuuint32_t es[3] = {1, 1, 1};
  enc(m, CU_TENSOR_MAP_DATA_TYPE_BFLOAT16, 3, const_cast<void*>(ptr), dims, strides, box, es, CU_TENSOR_MAP_INTERLEAVE_NONE,
      CU_TENSOR_MAP_SWIZZLE_128B, CU_TENSOR_MAP_L2_PROMOTION_L2_256B, CU_TENSOR_MAP_FLOAT_OOB_FILL_NONE);
}

void make_map_out(EncodeFn enc, CUtensorMap* m, const void* ptr, uint64_t ld) {
  cuuint64_t dims[3] = {64, 2048, ld / 64};
  cuuint64_t strides[2] = {ld * 2, 128};
  cuuint32_t box[3] = {64, 16, 2};
  cuuint32_t es[3] = {1, 1, 1};
  enc(m, CU_TENSOR_MAP_DATA_TYPE_BFLOAT16, 3, const_cast<void*>(ptr), dims, strides, box, es, CU_TENSOR_MAP_INTERLEAVE_NONE,
      CU_TENSOR_MAP_SWIZZLE_128B, CU_TENSOR_MAP_L2_PROMOTION_L2_256B, CU_TENSOR_MAP_FLOAT_OOB_FILL_NONE);
}

template <typename... Args>
void launch(void (*kern)(Args...), int grid, int block, int smem, bool pdl, Args... args) {
  cudaLaunchConfig_t cfg = {};
  cfg.gridDim = dim3(grid); cfg.blockDim = dim3(block); cfg.dynamicSmemBytes = smem; cfg.stream = cudaStreamPerThread;
  cudaLaunchAttribute at[1];
  at[0].id = cudaLaunchAttributeProgrammaticStreamSerialization;
  at[0].val.programmaticStreamSerializationAllowed = 1;
  cfg.attrs = at; cfg.numAttrs = pdl ? 1 : 0;
  cudaLaunchKernelEx(&cfg, kern, args...);
}

GemmMaps m1, m3;
AttnMaps m2;

}

extern "C" void kernel_launch(void* const* d_in, const int* in_sizes, int n_in, void* d_out, int out_size) {
  static void* cached[9] = {};
  bool same = true;
  for (int i = 0; i < 8; i++) same = same && cached[i] == d_in[i];
  same = same && cached[8] == d_out;
  if (!same) {
    void* fn = nullptr;
    cudaDriverEntryPointQueryResult qr;
    cudaGetDriverEntryPoint("cuTensorMapEncodeTiled", &fn, cudaEnableDefault, &qr);
    EncodeFn enc = (EncodeFn)fn;
    void *qkv, *o;
    cudaGetSymbolAddress(&qkv, g_qkv);
    cudaGetSymbolAddress(&o, g_o);
    const auto S128 = CU_TENSOR_MAP_SWIZZLE_128B, S64 = CU_TENSOR_MAP_SWIZZLE_64B;
    make_map(enc, &m1.a0, d_in[0], 1024, 2048, 1024, 64, 128, S128);
    make_map(enc, &m1.a1, d_in[3], 1024, 2048, 1024, 64, 128, S128);
    make_map(enc, &m1.w0, d_in[1], 3072, 1024, 3072, 64, 64, S128);
    make_map(enc, &m1.w1, d_in[4], 1024, 1024, 1024, 64, 64, S128);
    make_map(enc, &m1.w2, d_in[5], 32, 1024, 32, 32, 64, S64);
    make_map(enc, &m1.w3, d_in[6], 32, 1024, 32, 32, 64, S64);
    make_map_out(enc, &m1.out, qkv, QKV_LD);
    make_map(enc, &m1.outc, qkv, QKV_LD, 2048, QKV_LD, 64, 16, S128);
    make_map(enc, &m2.q, qkv, QKV_LD, 2048, QKV_LD, 32, 256, S64);
    make_map_kv(enc, &m2.kva, (__nv_bfloat16*)qkv + 1024, 1024, 1024);
    make_map_kv(enc, &m2.kvb, (__nv_bfloat16*)qkv + 4096, 32, 32);
    {
      static short unit[512];
      bool is_b[512] = {};
      int nb = 0, na = 0, left = 256 - A_GRID;
      for (int c = 0; c < A_GRID; c++) is_b[(h_first_step[c + 1] - 1) >> 4] = true;
      for (int len = 0; len <= 16; len++)
        for (int c = 0; c < A_GRID && left > 0; c++) {
          const int top = h_first_step[c + 1] - 1;
          if ((c < A_EARLY ? 0 : (top & 15) + 1) == len) { is_b[(top >> 4) - 1] = true; left--; }
        }
      for (int u = 0; u < 512; u++) unit[u] = is_b[u] ? 256 + nb++ : na++;
      for (int c = 0; c < A_GRID; c++) {
        const int top = h_first_step[c + 1] - 1, n = top + 1 - h_first_step[c];
        m2.rec[c * 8] = top; m2.rec[c * 8 + 1] = n;
        for (int i = 0; i < 6; i++) m2.rec[c * 8 + 2 + i] = unit[(top >> 4) - i < 0 ? 0 : (top >> 4) - i];
      }
    }
    make_map(enc, &m3.a0, o, O_LD, 2048, O_LD, 64, 128, S128);
    m3.a1 = m3.a0;
    make_map(enc, &m3.w0, d_in[2], 1024, 1024, 1024, 64, 64, S128);
    make_map(enc, &m3.w1, d_in[7], 1024, 1024, 1024, 64, 64, S128);
    m3.w2 = m3.w0; m3.w3 = m3.w0;
    make_map_out(enc, &m3.out, d_out, 2048);
    make_map(enc, &m3.outc, d_out, 2048, 2048, 2048, 64, 16, S128);
    make_map_w(enc, &m1.w0, d_in[1], 3072); make_map_w(enc, &m1.w1, d_in[4], 1024);
    make_map_w(enc, &m3.w0, d_in[2], 1024); make_map_w(enc, &m3.w1, d_in[7], 1024);
    cudaFuncSetAttribute(gemm_kernel<0>, cudaFuncAttributeMaxDynamicSharedMemorySize, G_SMEM);
    cudaFuncSetAttribute(gemm_kernel<1>, cudaFuncAttributeMaxDynamicSharedMemorySize, G_SMEM);
    cudaFuncSetAttribute(attn_kernel, cudaFuncAttributeMaxDynamicSharedMemorySize, A_SMEM);
    for (int i = 0; i < 8; i++) cached[i] = d_in[i];
    cached[8] = d_out;
  }
  launch(gemm_kernel<0>, 132, G_THREADS, G_SMEM, false, m1);
  launch(attn_kernel, A_GRID, A_THREADS, A_SMEM, true, m2);
  launch(gemm_kernel<1>, 128, G_THREADS, G_SMEM, true, m3);
}
```
